```python
import torch

def _softmax(x, axis=-1):
    return torch.softmax(x, dim=axis)
def _gelu(x):
    return torch.nn.functional.gelu(x, approximate="tanh")
def _silu(x):
    return torch.nn.functional.silu(x)
def _sigmoid(x):
    return torch.sigmoid(x)
def _layernorm(x, axis=-1, eps=1e-5):
    m = x.mean(dim=axis, keepdim=True)
    v = x.var(dim=axis, keepdim=True, unbiased=False)
    return (x - m) / torch.sqrt(v + eps)
def _scatter_add(tgt, idx, src, axis=0):
    return tgt.clone().index_add_(axis, idx, src)
def _segment_sum(src, seg, n):
    out = torch.zeros((n,) + src.shape[1:], dtype=src.dtype)
    return out.index_add_(0, seg, src)
def _pad(x, pw):
    flat = tuple(v for pair in reversed(pw) for v in pair)
    return torch.nn.functional.pad(x, flat)

kernel_name = 'interleave_layers__gqa_block_cached__dense_activation_gelu__decode'

def setup_inputs():

    _w = (lambda a: (lambda t: t.to(torch.bfloat16) if t.is_floating_point() else t)(torch.as_tensor(a)))
    def _A_setup():
        B, Sq, D = 1, 1, 448
        Hq, Hkv, Sk, Dh = 16, 8, 65536, 256
        assert Hq % Hkv == 0, (Hq, Hkv)
        return {
            "x": _w((lambda *s: torch.randn(*s, dtype=torch.bfloat16) * 0.05)(B, Sq, D)),
            "k_cache": _w((lambda *s: torch.randn(*s, dtype=torch.bfloat16) * 0.8)(B, Hkv, Sk, Dh)),
            "v_cache": _w((lambda *s: torch.randn(*s, dtype=torch.bfloat16) * 1.6)(B, Hkv, Sk, Dh)),
            "wq": _w((lambda *s: torch.randn(*s, dtype=torch.bfloat16) * 0.8)(D, Hq * Dh) * (D ** -0.5)),
            "wo": _w((lambda *s: torch.randn(*s, dtype=torch.bfloat16) * 1.6)(Hq * Dh, D) * ((Hq * Dh) ** -0.5)),
        }
    _A_in = _A_setup()

    def _B_setup():
        B, S, D, F = 1, 1, 448, 1792
        return {
            "x": _w((lambda *s: torch.randn(*s, dtype=torch.bfloat16) * 0.05)(B, S, D)),
            "w1": _w((lambda *s: torch.randn(*s, dtype=torch.bfloat16) * 0.2)(D, F) * (D ** -0.5)),
            "b1": _w((lambda *s: torch.randn(*s, dtype=torch.bfloat16) * 0.2)(F) * 0.01),
            "w2": _w((lambda *s: torch.randn(*s, dtype=torch.bfloat16) * 0.2)(F, D) * (F ** -0.5)),
            "b2": _w((lambda *s: torch.randn(*s, dtype=torch.bfloat16) * 0.2)(D) * 0.01),
        }
    _B_in = _B_setup()

    return {
        "A_x": _A_in["x"],
        "A_k_cache": _A_in["k_cache"],
        "A_v_cache": _A_in["v_cache"],
        "A_wq": _A_in["wq"],
        "A_wo": _A_in["wo"],
        "B_x": _B_in["x"],
        "B_w1": _B_in["w1"],
        "B_b1": _B_in["b1"],
        "B_w2": _B_in["w2"],
        "B_b2": _B_in["b2"],
    }

def reference(A_x, A_k_cache, A_v_cache, A_wq, A_wo, B_x, B_w1, B_b1, B_w2, B_b2):
    def _A_ref(x, k_cache, v_cache, wq, wo):
        B, Sq, D = x.shape
        Hq, Dh = 16, 256
        Hkv = k_cache.shape[1]
        rep = Hq // Hkv
        q = (lambda x, *d: x.permute(*d))((x @ wq).reshape(B, Sq, Hq, Dh), 0, 2, 1, 3)
        k = (lambda x, n, axis: torch.repeat_interleave(x, n, dim=axis))(k_cache, rep, axis=1)
        v = (lambda x, n, axis: torch.repeat_interleave(x, n, dim=axis))(v_cache, rep, axis=1)
        scores = torch.einsum("bhqd,bhkd->bhqk", q, k) * (Dh ** -0.5)
        p = _softmax(scores, axis=-1)
        o = torch.einsum("bhqk,bhkd->bhqd", p, v)
        return (lambda x, *d: x.permute(*d))(o, 0, 2, 1, 3).reshape(B, Sq, Hq * Dh) @ wo

    def _B_ref(x, w1, b1, w2, b2):
        h = torch.einsum("bsd,df->bsf", x, w1) + b1
        h = _gelu(h)
        return torch.einsum("bsf,fd->bsd", h, w2) + b2

    x = A_x
    x = x + _A_ref(_layernorm(x, axis=-1), A_k_cache, A_v_cache, A_wq, A_wo)
    x = x + _B_ref(_layernorm(x, axis=-1), B_w1, B_b1, B_w2, B_b2)
    x = x + _A_ref(_layernorm(x, axis=-1), A_k_cache, A_v_cache, A_wq, A_wo)
    x = x + _B_ref(_layernorm(x, axis=-1), B_w1, B_b1, B_w2, B_b2)
    return x
```

```cpp
#include <cuda_runtime.h>
#include <cuda_bf16.h>
#include <cuda.h>
#include <stdint.h>

namespace {

constexpr int D_MODEL = 448;
constexpr int HKV = 8;
constexpr int SK = 65536;
constexpr int DH = 256;
constexpr int NQ = 4096;
constexpr int FF = 1792;
constexpr int NROWS = HKV * SK;
constexpr int NTHREADS = 256;
constexpr int MAXG = 160;
constexpr int NMLP = 112;

#define KEEP_W 13312
#define KEEP_SKIP 1024
#define KEEP_M 2
#define KEEP_N 1
#define KEEP_FULL 3072
#define TB 4
#define TD 2

constexpr int W2_PITCH = 912;
constexpr int SM_RING = 0;
constexpr int SM_RES  = 65536;
constexpr int SM_WQ   = 131072;
constexpr int SM_WO   = SM_WQ + 28672;
constexpr int SM_W1   = SM_WO + 32 * W2_PITCH;
constexpr int SM_W2   = SM_W1 + 14336;
constexpr int SM_QF   = SM_W2 + 16 * W2_PITCH;
constexpr int SM_ACC  = SM_QF + 8192;
constexpr int SM_SC   = SM_ACC + 2048;
constexpr int SM_OC   = SM_SC + 1024;
constexpr int SM_ML   = SM_OC + 64;
constexpr int SM_ARR  = SM_ML + 16;
constexpr int SM_EP   = SM_ARR + 64;
constexpr int SM_XK   = SM_EP + 16;
constexpr int SM_ST   = SM_XK + 96;
constexpr int SM_BAR  = SM_ST + 128;
constexpr int SM_CH   = SM_BAR + 8 * 3 * 8;
constexpr int SM_DUM  = SM_CH + 64;
constexpr int SM_TOTAL = SM_DUM + 128;
static_assert(SM_DUM % 16 == 0, "align");
static_assert(SM_TOTAL <= 232448, "smem");

__device__ __align__(128) uint4 g_part[4 * MAXG * 128];
__device__ __align__(128) uint4 g_x[NMLP];
__device__ __align__(128) uint4 g_q[1024];
__device__ __align__(128) unsigned int g_ticket[32];
__device__ __align__(128) unsigned int g_epoch[32];

constexpr int SPIN_LIMIT = 1 << 22;

__device__ __forceinline__ uint32_t smem_u32(const void* p) { return (uint32_t)__cvta_generic_to_shared(p); }
__device__ __forceinline__ void mbar_init(uint32_t bar, uint32_t cnt) {
    asm volatile("mbarrier.init.shared::cta.b64 [%0], %1;" :: "r"(bar), "r"(cnt) : "memory");
}
__device__ __forceinline__ void mbar_expect_tx(uint32_t bar, uint32_t bytes) {
    asm volatile("mbarrier.arrive.expect_tx.shared::cta.b64 _, [%0], %1;" :: "r"(bar), "r"(bytes) : "memory");
}
__device__ __forceinline__ void mbar_arrive(uint32_t bar) {
    asm volatile("mbarrier.arrive.shared::cta.b64 _, [%0];" :: "r"(bar) : "memory");
}
__device__ __forceinline__ void mbar_wait(uint32_t bar, uint32_t parity) {
    uint32_t ok;
    int it = 0;
    do {
        asm volatile("{\n.reg .pred p;\nmbarrier.try_wait.parity.shared::cta.b64 p, [%1], %2;\nselp.u32 %0, 1, 0, p;\n}"
                     : "=r"(ok) : "r"(bar), "r"(parity) : "memory");
        if (++it > SPIN_LIMIT) __trap();
    } while (!ok);
}
__device__ __forceinline__ void tma_tile(uint32_t dst, const CUtensorMap* tm, int row, uint32_t bar, uint64_t pol) {
    asm volatile("cp.async.bulk.tensor.3d.shared::cluster.global.mbarrier::complete_tx::bytes.L2::cache_hint"
                 " [%0], [%1, {%2, %3, %4}], [%5], %6;"
                 :: "r"(dst), "l"(tm), "r"(0), "r"(row), "r"(0), "r"(bar), "l"(pol) : "memory");
}
__device__ __forceinline__ void l2_prefetch(const void* p, uint32_t bytes, uint64_t pol) {
    asm volatile("cp.async.bulk.prefetch.L2.global.L2::cache_hint [%0], %1, %2;" :: "l"(p), "r"(bytes), "l"(pol) : "memory");
}
__device__ __forceinline__ uint64_t pol_first() {
    uint64_t p; asm volatile("createpolicy.fractional.L2::evict_first.b64 %0, 1.0;" : "=l"(p)); return p;
}
__device__ __forceinline__ uint64_t pol_normal() {
    uint64_t p; asm volatile("createpolicy.fractional.L2::evict_normal.b64 %0, 1.0;" : "=l"(p)); return p;
}
__device__ __forceinline__ void cp_async16(uint32_t dst, const void* src) {
    asm volatile("cp.async.cg.shared.global [%0], [%1], 16;" :: "r"(dst), "l"(src) : "memory");
}
__device__ __forceinline__ void cp_async4_hint(uint32_t dst, const void* src, uint64_t pol) {
    asm volatile("cp.async.ca.shared.global.L2::cache_hint [%0], [%1], 4, %2;" :: "r"(dst), "l"(src), "l"(pol) : "memory");
}
__device__ __forceinline__ void ldsm4(uint32_t* r, uint32_t addr) {
    asm volatile("ldmatrix.sync.aligned.m8n8.x4.shared.b16 {%0,%1,%2,%3}, [%4];"
                 : "=r"(r[0]), "=r"(r[1]), "=r"(r[2]), "=r"(r[3]) : "r"(addr) : "memory");
}
__device__ __forceinline__ void ldsm4t(uint32_t* r, uint32_t addr) {
    asm volatile("ldmatrix.sync.aligned.m8n8.x4.trans.shared.b16 {%0,%1,%2,%3}, [%4];"
                 : "=r"(r[0]), "=r"(r[1]), "=r"(r[2]), "=r"(r[3]) : "r"(addr) : "memory");
}
__device__ __forceinline__ void lds128(uint32_t* r, uint32_t addr) {
    asm volatile("ld.volatile.shared.v4.u32 {%0,%1,%2,%3}, [%4];" : "=r"(r[0]), "=r"(r[1]), "=r"(r[2]), "=r"(r[3]) : "r"(addr) : "memory");
}
__device__ __forceinline__ void mma16816(float* c, const uint32_t* a, uint32_t b0, uint32_t b1) {
    asm volatile("mma.sync.aligned.m16n8k16.row.col.f32.bf16.bf16.f32 {%0,%1,%2,%3}, {%4,%5,%6,%7}, {%8,%9}, {%0,%1,%2,%3};"
                 : "+f"(c[0]), "+f"(c[1]), "+f"(c[2]), "+f"(c[3])
                 : "r"(a[0]), "r"(a[1]), "r"(a[2]), "r"(a[3]), "r"(b0), "r"(b1));
}
__device__ __forceinline__ void mma1688(float* c, uint32_t a0, uint32_t a1, uint32_t b0) {
    asm volatile("mma.sync.aligned.m16n8k8.row.col.f32.bf16.bf16.f32 {%0,%1,%2,%3}, {%4,%5}, {%6}, {%0,%1,%2,%3};"
                 : "+f"(c[0]), "+f"(c[1]), "+f"(c[2]), "+f"(c[3])
                 : "r"(a0), "r"(a1), "r"(b0));
}
__device__ __forceinline__ float ex2(float x) { float y; asm("ex2.approx.ftz.f32 %0, %1;" : "=f"(y) : "f"(x)); return y; }
__device__ __forceinline__ float bf16r(float x) { return __bfloat162float(__float2bfloat16_rn(x)); }
__device__ __forceinline__ float bf_lo(uint32_t w) { return __uint_as_float(w << 16); }
__device__ __forceinline__ float bf_hi(uint32_t w) { return __uint_as_float(w & 0xffff0000u); }
__device__ __forceinline__ uint32_t pack_bf16(float lo, float hi) {
    uint32_t r; asm("cvt.rn.bf16x2.f32 %0, %1, %2;" : "=r"(r) : "f"(hi), "f"(lo)); return r;
}

__device__ __forceinline__ void pk_store(uint4* p, uint32_t w0, uint32_t w1, uint32_t w2, uint32_t w3) {
    asm volatile("{\n.reg .b128 v;\nmov.b128 v, {%1, %2};\nst.relaxed.gpu.global.b128 [%0], v;\n}"
                 :: "l"(p), "l"(((uint64_t)w1 << 32) | w0), "l"(((uint64_t)w3 << 32) | w2) : "memory");
}
__device__ __forceinline__ uint4 pk_load(const uint4* p) {
    uint64_t a, b;
    asm volatile("{\n.reg .b128 v;\nld.relaxed.gpu.global.b128 v, [%2];\nmov.b128 {%0, %1}, v;\n}" : "=l"(a), "=l"(b) : "l"(p) : "memory");
    return make_uint4((uint32_t)a, (uint32_t)(a >> 32), (uint32_t)b, (uint32_t)(b >> 32));
}
__device__ __forceinline__ uint4 pk_poll(const uint4* p, bool active, uint32_t tag, uint4 v) {
    bool ok = !active;
    int it = 0;
    do {
        if (!ok) { v = pk_load(p); ok = (v.z >> 16) == tag; }
        if (++it > SPIN_LIMIT) __trap();
    } while (!__all_sync(0xffffffffu, ok));
    return v;
}
__device__ __forceinline__ void part_store(uint4* p, float v0, float v1, float v2, float v3, float lse, uint32_t tag) {
    const uint32_t u0 = (__float_as_uint(v0) + 0x800u) >> 12, u1 = (__float_as_uint(v1) + 0x800u) >> 12;
    const uint32_t u2 = (__float_as_uint(v2) + 0x800u) >> 12, u3 = (__float_as_uint(v3) + 0x800u) >> 12;
    pk_store(p, u0 | (u1 << 20), (u1 >> 12) | (u2 << 8) | (u3 << 28), (u3 >> 4) | (tag << 16), __float_as_uint(lse));
}
__device__ __forceinline__ void part_decode(uint4 v, float w, float& c0, float& c1, float& c2, float& c3) {
    c0 = fmaf(w, __uint_as_float(v.x << 12), c0);
    c1 = fmaf(w, __uint_as_float(__funnelshift_r(v.x, v.y, 20) << 12), c1);
    c2 = fmaf(w, __uint_as_float((v.y << 4) & 0xfffff000u), c2);
    c3 = fmaf(w, __uint_as_float(__funnelshift_r(v.y, v.z, 28) << 12), c3);
}
__device__ __forceinline__ float lg2(float x) { float y; asm("lg2.approx.ftz.f32 %0, %1;" : "=f"(y) : "f"(x)); return y; }
__device__ __forceinline__ void spin_clk(uint32_t clk) { uint32_t c0 = clock(); while ((uint32_t)clock() - c0 < clk) {} }
__device__ __forceinline__ uint32_t ticket_fetch(uint32_t n) {
    uint32_t r;
    asm volatile("{\n.reg .u32 l;\n.reg .u64 a;\nmov.u32 l, %%laneid;\nmad.wide.u32 a, l, 4, %1;\natom.relaxed.gpu.global.add.u32 %0, [a], %2;\n}"
                 : "=r"(r) : "l"(&g_ticket[0]), "r"(n) : "memory");
    return r;
}
__device__ __forceinline__ int tid_now() { int t; asm volatile("mov.u32 %0, %%tid.x;" : "=r"(t)); return t; }
__device__ __forceinline__ float rcp_fast(float x) { float y; asm("rcp.approx.ftz.f32 %0, %1;" : "=f"(y) : "f"(x)); return y; }
__device__ __forceinline__ unsigned long long gtime() { unsigned long long t; asm volatile("mov.u64 %0, %globaltimer;" : "=l"(t)); return t; }
#define TSTAMP(i) do {} while (0)
#define WSTAMP(i) do {} while (0)

constexpr float SCALE_LOG2E = 0.0625f * 1.4426950408889634f;
constexpr float M_INIT = -3.0e38f;

struct Params {
    const __nv_bfloat16* x0;
    const __nv_bfloat16* kc;
    const __nv_bfloat16* vc;
    const __nv_bfloat16* wq;
    const __nv_bfloat16* wo;
    const __nv_bfloat16* w1;
    const __nv_bfloat16* b1;
    const __nv_bfloat16* w2;
    const __nv_bfloat16* b2;
    __nv_bfloat16* out;
    uint32_t hmagic;
};

__device__ __forceinline__ uint32_t softmax_step(float s0, float s1, float& m, float& l, float* o, int lane) {
    float mx = fmaxf(s0, s1);
    if (__any_sync(0xffffffffu, mx > m)) {
        mx = fmaxf(mx, __shfl_xor_sync(0xffffffffu, mx, 1));
        mx = fmaxf(mx, __shfl_xor_sync(0xffffffffu, mx, 2));
        float mn = fmaxf(m, mx);
        float corr = ex2((m - mn) * SCALE_LOG2E);
        float corr_o = __shfl_xor_sync(0xffffffffu, corr, 4);
        float c0 = (lane & 4) ? corr_o : corr;
        float c1 = (lane & 4) ? corr : corr_o;
        m = mn;
        l *= corr;
#pragma unroll
        for (int i = 0; i < 16; i += 2) { o[i] *= c0; o[i + 1] *= c1; }
    }
    const float mc = m * SCALE_LOG2E;
    float p0 = ex2(fmaf(s0, SCALE_LOG2E, -mc));
    float p1 = ex2(fmaf(s1, SCALE_LOG2E, -mc));
    l += p0 + p1;
    return pack_bf16(p0, p1);
}

__device__ __forceinline__ void qk_smem(uint32_t a0, uint32_t qaddr, float& s0, float& s1) {
    float e[4] = {0.f, 0.f, 0.f, 0.f}, od[4] = {0.f, 0.f, 0.f, 0.f};
#pragma unroll 1
    for (int c = 0; c < 4; c++) {
        uint32_t b0[4], b1[4], q0[4], q1[4];
        ldsm4(b0, a0);
        lds128(q0, qaddr);
        ldsm4(b1, a0 ^ 64u);
        lds128(q1, qaddr + 128);
        mma16816(e, q0, b0[0], b0[1]);
        mma16816(od, q0, b0[2], b0[3]);
        mma16816(e, q1, b1[0], b1[1]);
        mma16816(od, q1, b1[2], b1[3]);
        a0 += 1024; qaddr += 256;
    }
    s0 = e[0] + od[2]; s1 = e[1] + od[3];
}
__device__ __forceinline__ void qk_regs(const uint32_t* kf, uint32_t qaddr, float& s0, float& s1) {
    float e[4] = {0.f, 0.f, 0.f, 0.f}, od[4] = {0.f, 0.f, 0.f, 0.f};
#pragma unroll
    for (int n = 0; n < 8; n++) {
        uint32_t a[4];
        lds128(a, qaddr + n * 128);
        mma16816(e, a, kf[4 * n], kf[4 * n + 1]);
        mma16816(od, a, kf[4 * n + 2], kf[4 * n + 3]);
    }
    s0 = e[0] + od[2]; s1 = e[1] + od[3];
}
__device__ __forceinline__ void pv_smem(uint32_t a0, uint32_t P, float* o, int lane) {
    int gj = lane >> 3;
#pragma unroll 1
    for (int h = 0; h < 2; h++) {
        const uint32_t P0 = gj == 0 ? P : 0u, P1 = gj == 1 ? P : 0u;
        uint32_t a[4][4];
#pragma unroll
        for (int i = 0; i < 4; i++) ldsm4t(a[i], a0 + i * 1024);
#pragma unroll
        for (int i = 0; i < 4; i++) mma1688(o + 4 * i, a[i][0], a[i][1], P0);
#pragma unroll
        for (int i = 0; i < 4; i++) mma1688(o + 4 * i, a[i][2], a[i][3], P1);
        a0 ^= 64u; gj -= 2;
    }
}
__device__ __forceinline__ void pv_regs(const uint32_t* vf, uint32_t P, float* o, int lane) {
    int gj = lane >> 3;
    uint32_t Pj[4];
#pragma unroll
    for (int j = 0; j < 4; j++) Pj[j] = (gj == j) ? P : 0u;
#pragma unroll
    for (int nn = 0; nn < 8; nn++) {
        const int n = ((nn & 3) << 1) | (nn >> 2);
        mma1688(o + 4 * (n >> 1), vf[4 * n], vf[4 * n + 1], Pj[2 * (n & 1)]);
        mma1688(o + 4 * (n >> 1), vf[4 * n + 2], vf[4 * n + 3], Pj[2 * (n & 1) + 1]);
    }
}

__device__ __forceinline__ void ln_stats(const float* st, float& mb, float& rsd) {
    const float4 v0 = *reinterpret_cast<const float4*>(st), v1 = *reinterpret_cast<const float4*>(st + 4);
    const float4 v2 = *reinterpret_cast<const float4*>(st + 8);
    const float2 v3 = *reinterpret_cast<const float2*>(st + 12);
    const double s = (((double)v0.x + (double)v0.z) + ((double)v1.x + (double)v1.z)) + (((double)v2.x + (double)v2.z) + (double)v3.x);
    const double q = (((double)v0.y + (double)v0.w) + ((double)v1.y + (double)v1.w)) + (((double)v2.y + (double)v2.w) + (double)v3.y);
    double mean = s * (1.0 / D_MODEL);
    double var = fma(-mean, mean, q * (1.0 / D_MODEL));
    mb = bf16r((float)mean);
    float vb = bf16r(fmaxf((float)var, 0.f));
    float sd; asm("sqrt.approx.ftz.f32 %0, %1;" : "=f"(sd) : "f"(bf16r(vb + 1e-5f)));
    rsd = rcp_fast(bf16r(sd));
}

__device__ __forceinline__ float warp_max(float v) {
#pragma unroll
    for (int of = 16; of; of >>= 1) v = fmaxf(v, __shfl_xor_sync(0xffffffffu, v, of));
    return v;
}
__device__ __forceinline__ void warp_sum5(float& a, float& b, float& c, float& d, float& e) {
#pragma unroll
    for (int of = 16; of; of >>= 1) {
        a += __shfl_xor_sync(0xffffffffu, a, of); b += __shfl_xor_sync(0xffffffffu, b, of);
        c += __shfl_xor_sync(0xffffffffu, c, of); d += __shfl_xor_sync(0xffffffffu, d, of);
        e += __shfl_xor_sync(0xffffffffu, e, of);
    }
}

__device__ __forceinline__ void poll_x(int warp, int lane, uint32_t tag, uint32_t* xb) {
    const uint4 v = pk_poll(g_x + warp * 16 + lane, lane < 16, tag, make_uint4(0, 0, 0, 0));
#pragma unroll
    for (int j = 0; j < 4; j++) {
        xb[2 * j] = __shfl_sync(0xffffffffu, v.x, j * 4 + (lane & 3));
        xb[2 * j + 1] = __shfl_sync(0xffffffffu, v.y, j * 4 + (lane & 3));
    }
}
__device__ __forceinline__ void lazy_wait(const uint4* p, uint32_t tag) {
    if (threadIdx.x == 0) {
        int it = 0;
        while ((pk_load(p).z >> 16) != tag) { __nanosleep(100); if (++it > SPIN_LIMIT) __trap(); }
    }
    __syncthreads();
}

#define RS_DST (g_part + ((warp * 4 + (lane & 3)) * 4 + ((lane >> 2) & 3)) * 256 + cta * 2 + (lane >> 4))
#define RS_SRC (g_part + cta * 256 + tid)
#define TAG_BASE(pass_) ((*epw * 32 + (pass_) * 16) & 0xffffu)
constexpr uint32_t TAG_PART = 1, TAG_R1 = 9, TAG_X1 = 10, TAG_R2 = 11, TAG_X2 = 12, TAG_Q = 13;
#define DLY_R 400
#define DLY_X 300
#define DLY_Q 300

__device__ __forceinline__ int take_position(volatile uint32_t* stw, int lane, uint32_t& k, uint32_t& tnext) {
    k = 0;
    if (lane == 0) k = atomicAdd(const_cast<uint32_t*>(stw) + 24, 1u);
    k = __shfl_sync(0xffffffffu, k, 0);
    tnext = 0;
    if (lane == 0 && k % TB == 0) tnext = ticket_fetch(TB);
    const uint32_t b = k / TB;
    uint32_t w;
    int it = 0;
    while (((w = stw[8 + (b & 15)]) & 0xfffu) != (b >> 4)) { if (++it > SPIN_LIMIT) __trap(); }
    return (int)(w >> 12) + (int)(k % TB);
}
__device__ __forceinline__ void take_publish(volatile uint32_t* stw, int lane, uint32_t k, uint32_t tnext, int G) {
    if (lane == 0 && k % TB == 0) {
        const uint32_t b = k / TB + TD;
        stw[8 + (b & 15)] = ((tnext + G * (TB * TD)) << 12) | (b >> 4);
    }
}

#define PHASE_IDS const int tid = tid_now(), warp = __shfl_sync(0xffffffffu, tid >> 5, 0), lane = tid & 31; (void)warp; (void)lane;
#define RING_IDS \
    const uint32_t barK = sb + SM_BAR + warp * 24, barV = barK + 8, barR = barK + 16; (void)barR; \
    const uint32_t slotK = sb + SM_RING + warp * 8192, slotV = slotK + 4096; \
    const uint32_t lmoff = (lane & 7) * 128 + ((((lane >> 3) ^ lane) & 7) << 4); (void)lmoff;

__global__ void __launch_bounds__(NTHREADS, 1)
fused_kernel(const __grid_constant__ CUtensorMap tmK, const __grid_constant__ CUtensorMap tmV, const Params prm) {
    extern __shared__ __align__(1024) unsigned char smem[];
    const int cta = blockIdx.x, G = gridDim.x;
    const uint32_t sb = smem_u32(smem);
    const int RPH = G * 4;
    const int NS = 8 * (SK / 8 - RPH);
    const uint32_t hmagic = prm.hmagic;
    volatile uint32_t* const stw = reinterpret_cast<volatile uint32_t*>(smem + SM_ST);
    volatile uint32_t* const epw = reinterpret_cast<volatile uint32_t*>(smem + SM_EP);
    float* const acc = reinterpret_cast<float*>(smem + SM_ACC);
    float* const sc = reinterpret_cast<float*>(smem + SM_SC);
    uint32_t* const oc = reinterpret_cast<uint32_t*>(smem + SM_OC);
    float* const accml = reinterpret_cast<float*>(smem + SM_ML);
    float* const xk = reinterpret_cast<float*>(smem + SM_XK);
    TSTAMP(0);

    {
    PHASE_IDS
    if (cta < 128) {
#pragma unroll
        for (int k = 0; k < 7; k++) {
            int c = tid + k * 256;
            cp_async16(sb + SM_WQ + c * 16, prm.wq + (size_t)(c >> 2) * NQ + cta * 32 + (c & 3) * 8);
        }
    }
    asm volatile("cp.async.commit_group;" ::: "memory");
    uint32_t epoch = 0;
    if (tid == 17) epoch = *reinterpret_cast<volatile unsigned int*>(&g_epoch[0]);
    RING_IDS
    const int res_row = (warp & 1) * SK + (cta * 4 + (warp >> 1)) * 8;
    if (lane == 0) {
        mbar_init(barK, 1); mbar_init(barV, 1); mbar_init(barR, 1); mbar_init(sb + SM_CH + warp * 8, 1);
        asm volatile("fence.mbarrier_init.release.cluster;" ::: "memory");
        asm volatile("fence.proxy.async.shared::cta;" ::: "memory");
        uint64_t pf = pol_first();
        mbar_expect_tx(barK, 4096); tma_tile(slotK, &tmK, res_row, barK, pf);
        mbar_expect_tx(barV, 4096); tma_tile(slotV, &tmV, res_row, barV, pf);
        mbar_expect_tx(barR, 8192);
        tma_tile(sb + SM_RES + warp * 8192, &tmK, res_row + 6 * SK, barR, pf);
        tma_tile(sb + SM_RES + warp * 8192 + 4096, &tmV, res_row + 6 * SK, barR, pf);
    }
    if (tid < 16) reinterpret_cast<unsigned int*>(smem + SM_ARR)[tid] = 0;
    if (cta < 128) {
        const int h = cta >> 6, b = (cta >> 5) & 1, cl = cta & 31;
        const int dbase = h * 256 + 16 * (cl & 3) + (cl >> 2) + 8 * b;
#pragma unroll
        for (int k = 0; k < 7; k++) {
            int c = tid + k * 256;
            int lr = c / 56, cc = c - lr * 56;
            int grow = (lr >> 2) * 512 + (lr & 3) * 64 + dbase;
            cp_async16(sb + SM_WO + lr * W2_PITCH + cc * 16, prm.wo + (size_t)grow * D_MODEL + cc * 8);
        }
    }
    if (cta < NMLP) {
#pragma unroll
        for (int k = 0; k < 4; k++) {
            int c = tid + k * 256;
            if (c < 896) {
                int lr = c / 56, cc = c - lr * 56;
                cp_async16(sb + SM_W1 + c * 16, prm.w1 + (size_t)(c >> 1) * FF + cta * 16 + (c & 1) * 8);
                cp_async16(sb + SM_W2 + lr * W2_PITCH + cc * 16, prm.w2 + (size_t)cta * 16 * D_MODEL + c * 8);
            }
        }
    }
    asm volatile("cp.async.commit_group;" ::: "memory");
    if (cta < NMLP && tid < 24) {
        const int c = 16 * (cta >> 2) + (cta & 3) + 4 * ((tid >> 1) & 1) + 8 * (tid & 1);
        xk[tid] = __bfloat162float(tid < 4 ? prm.x0[c] : tid < 8 ? prm.b2[c] : prm.b1[cta * 16 + tid - 8]);
    }
    if (tid == 17) *epw = epoch;
    if (tid >= 32 && tid < 48) stw[tid - 24] = tid - 32 < TD ? (uint32_t)((cta * TD + tid - 32) * TB) << 12 : 0xfffu;
    if (tid == 48) stw[24] = 0;
    asm volatile("cp.async.wait_group 1;" ::: "memory");
    }
    __syncthreads();

    uint32_t rk[3][32], rv[3][32];

#pragma unroll 1
    for (int pass = 0; pass < 2; pass++) {
        if (cta < 128) {
            PHASE_IDS
            const uint32_t tb = TAG_BASE(pass);
            if (pass == 1 && cta >= NMLP) lazy_wait(g_x + (cta - NMLP), tb - 16 + TAG_X2);
            if (warp < 7) {
                const uint32_t wa = sb + SM_WQ + (warp * 64 + ((lane & 7) >> 1) + 8 * (lane & 1) + 4 * (lane >> 4)) * 64 + ((lane >> 3) & 1) * 16;
                uint32_t af[4][4];
#pragma unroll
                for (int j = 0; j < 4; j++) ldsm4t(af[j], wa + j * 1024);
                uint32_t xb[8];
                if (pass == 0) {
                    const unsigned short* xp = reinterpret_cast<const unsigned short*>(prm.x0) + warp * 64 + (lane & 3);
#pragma unroll
                    for (int j = 0; j < 8; j++) xb[j] = (uint32_t)xp[(j >> 1) * 16 + (j & 1) * 4] | ((uint32_t)xp[(j >> 1) * 16 + (j & 1) * 4 + 8] << 16);
                } else {
                    if (cta < NMLP) spin_clk(DLY_X);
                    poll_x(warp, lane, tb - 16 + TAG_X2, xb);
                }
                if (pass == 1) TSTAMP(30);
                const bool ones = (lane >> 2) == 1;
                float d0[4] = {0.f, 0.f, 0.f, 0.f}, d1[4] = {0.f, 0.f, 0.f, 0.f}, ds[4] = {0.f, 0.f, 0.f, 0.f};
#pragma unroll
                for (int j = 0; j < 4; j++) {
                    uint32_t b0 = ones ? 0x3f803f80u : xb[2 * j], b1 = ones ? 0x3f803f80u : xb[2 * j + 1];
                    uint32_t a2[4] = {0x3f803f80u, xb[2 * j], 0x3f803f80u, xb[2 * j + 1]};
                    uint32_t ag[4];
                    ldsm4t(ag, wa + j * 1024 + 32);
                    mma16816(d0, af[j], b0, b1);
                    mma16816(ds, a2, b0, b1);
                    mma16816(d1, ag, b0, b1);
                }
                if ((lane & 3) == 0) {
                    const int g = lane >> 2;
                    float2* pp = reinterpret_cast<float2*>(acc) + warp * 32;
                    pp[g] = make_float2(d0[0], d0[1]); pp[g + 8] = make_float2(d0[2], d0[3]);
                    pp[g + 16] = make_float2(d1[0], d1[1]); pp[g + 24] = make_float2(d1[2], d1[3]);
                    if (lane == 0) *reinterpret_cast<float2*>(sc + 2 * warp) = make_float2(ds[0], ds[2]);
                }
            }
            __syncthreads();
            if (pass == 1) TSTAMP(31);
            if (warp == 0) {
                float mb, rsd;
                ln_stats(sc, mb, rsd);
                float2 v[7];
#pragma unroll
                for (int w = 0; w < 7; w++) v[w] = *reinterpret_cast<const float2*>(acc + w * 64 + lane * 2);
                const float s0 = ((v[0].x + v[1].x) + (v[2].x + v[3].x)) + ((v[4].x + v[5].x) + v[6].x);
                const float w0 = ((v[0].y + v[1].y) + (v[2].y + v[3].y)) + ((v[4].y + v[5].y) + v[6].y);
                const float qv = fmaf(-mb, w0, s0) * rsd;
                const uint32_t pr = pack_bf16(qv, __shfl_down_sync(0xffffffffu, qv, 1));
                const uint32_t pr2 = __shfl_down_sync(0xffffffffu, pr, 2);
                if ((lane & 3) == 0) pk_store(g_q + cta * 8 + (lane >> 2), pr, pr2, (tb + TAG_Q) << 16, 0);
            }
        }
        TSTAMP(pass * 32 + 1);
        if (pass == 0) {
            PHASE_IDS
            RING_IDS
#pragma unroll
            for (int i = 0; i < 3; i++) {
                const uint32_t ph = i & 1;
                int nrow;
                if (i < 2) nrow = ((warp & 1) + 2 * (i + 1)) * SK + (cta * 4 + (warp >> 1)) * 8;
                else {
                    uint32_t k, tnext;
                    const int p0 = take_position(stw, lane, k, tnext);
                    nrow = (p0 + RPH) * 8;
                    if (lane == 0) stw[warp] = p0 * 2 + 1;
                    take_publish(stw, lane, k, tnext, G);
                }
                mbar_wait(barK, ph);
#pragma unroll
                for (int n = 0; n < 8; n++) ldsm4(&rk[i][4 * n], slotK + ((n & 1) ? (lmoff ^ 64u) : lmoff) + (n >> 1) * 1024);
                __syncwarp();
                if (lane == 0) { mbar_expect_tx(barK, 4096); tma_tile(slotK, &tmK, nrow, barK, pol_first()); }
                mbar_wait(barV, ph);
#pragma unroll
                for (int n = 0; n < 8; n++) ldsm4t(&rv[i][4 * n], slotV + ((n & 1) ? (lmoff ^ 64u) : lmoff) + (n >> 1) * 1024);
                __syncwarp();
                if (lane == 0) { mbar_expect_tx(barV, 4096); tma_tile(slotV, &tmV, nrow, barV, pol_first()); }
            }
        }
        {
            PHASE_IDS
            const uint32_t tb = TAG_BASE(pass);
            if (cta >= 128) lazy_wait(g_q + cta, tb + TAG_Q);
            else if (pass == 1) spin_clk(DLY_Q);
            uint4 qv[4];
            int it = 0;
            while (true) {
#pragma unroll
                for (int k = 0; k < 4; k++) qv[k] = pk_load(g_q + tid + k * 256);
                const uint32_t t16 = tb + TAG_Q;
                if (__all_sync(0xffffffffu, (qv[0].z >> 16) == t16 && (qv[1].z >> 16) == t16 && (qv[2].z >> 16) == t16 && (qv[3].z >> 16) == t16)) break;
                if (++it > SPIN_LIMIT) __trap();
            }
            const int col = tid * 4, h = (col >> 8) & 1, d = col & 255;
            const int n = d >> 5, quarter = (d >> 3) & 3, t = (d & 7) >> 1;
            const int w = ((quarter & 1) << 1) | (quarter >> 1);
            uint32_t* dst = reinterpret_cast<uint32_t*>(smem + SM_QF + (col >> 9) * 1024 + n * 128 + (h * 4 + t) * 16 + w * 4);
#pragma unroll
            for (int k = 0; k < 4; k++) { dst[k * 512] = qv[k].x; dst[k * 512 + 4] = qv[k].y; }
        }
        __syncthreads();
        TSTAMP(pass * 32 + 2);

        const int hx = pass ? 7 : 0;
        {
        PHASE_IDS
        RING_IDS
        const uint32_t qlane = sb + SM_QF + (((lane >> 2) & 1) * 4 + (lane & 3)) * 16;
        int ps = stw[warp];
        float o[16];
#pragma unroll
        for (int i = 0; i < 16; i++) o[i] = 0.f;
        float m = M_INIT, l = 0.f;
        int cur_seq = 0;
        int res_state = ((hx ^ warp) & 1) ? 2 : 0;
#pragma unroll 1
        while (true) {
            const int pcur = ps >> 1;
            const bool more = pcur < (pass + 1) * NS;
            if (!more) WSTAMP(pass * 32 + 18 + warp);
            const int seq = more ? (int)(__umulhi((uint32_t)(pass ? 2 * NS - 1 - pcur : pcur), hmagic) ^ hx) : 8;
#pragma unroll 1
            while (true) {
                if (res_state == 1 || (res_state == 0 && cur_seq < seq)) {
                    res_state = 2;
                    const int head = cur_seq ^ hx;
                    const uint32_t qa = qlane + head * 1024;
                    float s0, s1;
                    if (head < 2) {
                        qk_regs(rk[0], qa, s0, s1);
                        pv_regs(rv[0], softmax_step(s0, s1, m, l, o, lane), o, lane);
                    } else if (head < 4) {
                        qk_regs(rk[1], qa, s0, s1);
                        pv_regs(rv[1], softmax_step(s0, s1, m, l, o, lane), o, lane);
                    } else if (head < 6) {
                        qk_regs(rk[2], qa, s0, s1);
                        pv_regs(rv[2], softmax_step(s0, s1, m, l, o, lane), o, lane);
                    } else {
                        mbar_wait(barR, 0);
                        qk_smem(sb + SM_RES + warp * 8192 + lmoff, qa, s0, s1);
                        pv_smem(sb + SM_RES + warp * 8192 + 4096 + lmoff, softmax_step(s0, s1, m, l, o, lane), o, lane);
                    }
                }
                if (cur_seq >= seq) break;
                const uint32_t tb = TAG_BASE(pass);
                l += __shfl_xor_sync(0xffffffffu, l, 1);
                l += __shfl_xor_sync(0xffffffffu, l, 2);
                float m0 = __shfl_sync(0xffffffffu, m, 0), m1 = __shfl_sync(0xffffffffu, m, 4);
                float l0 = __shfl_sync(0xffffffffu, l, 0), l1 = __shfl_sync(0xffffffffu, l, 4);
                const int hid = pass * 8 + cur_seq;
                uint32_t idx = 0;
                if (lane == 0) idx = atomicAdd(reinterpret_cast<unsigned int*>(smem + SM_ARR) + hid, 1u);
                idx = __shfl_sync(0xffffffffu, idx, 0);
                if (idx != 0) mbar_wait(sb + SM_CH + (idx - 1) * 8, hid & 1);
                else if (hid != 0) mbar_wait(sb + SM_CH + 56, (hid - 1) & 1);
                if (cur_seq == 7 && idx == 0) WSTAMP(pass * 32 + 3);
                if (idx != 0) {
                    const float4 aml = *reinterpret_cast<const float4*>(accml);
                    const float am0 = aml.x, am1 = aml.y, al0 = aml.z, al1 = aml.w;
                    float n0 = fmaxf(m0, am0), n1 = fmaxf(m1, am1);
                    float sa0 = ex2((am0 - n0) * SCALE_LOG2E), sb0 = ex2((m0 - n0) * SCALE_LOG2E);
                    float sa1 = ex2((am1 - n1) * SCALE_LOG2E), sb1 = ex2((m1 - n1) * SCALE_LOG2E);
                    m0 = n0; m1 = n1;
                    l0 = l0 * sb0 + al0 * sa0; l1 = l1 * sb1 + al1 * sa1;
#pragma unroll
                    for (int i = 0; i < 16; i += 4) {
                        const float4 v = reinterpret_cast<const float4*>(acc)[i * 8 + lane];
                        o[i] = o[i] * sb0 + v.x * sa0; o[i + 1] = o[i + 1] * sb1 + v.y * sa1;
                        o[i + 2] = o[i + 2] * sb0 + v.z * sa0; o[i + 3] = o[i + 3] * sb1 + v.w * sa1;
                    }
                    __syncwarp();
                }
                if (idx != 7) {
#pragma unroll
                    for (int i = 0; i < 16; i += 4) reinterpret_cast<float4*>(acc)[i * 8 + lane] = make_float4(o[i], o[i + 1], o[i + 2], o[i + 3]);
                    if (lane == 0) *reinterpret_cast<float4*>(accml) = make_float4(m0, m1, l0, l1);
                    __syncwarp();
                }
                if (lane == 0) mbar_arrive(sb + SM_CH + idx * 8);
                if (idx == 7) {
                    uint4* dst = g_part + ((cur_seq & 3) * G + cta) * 128 + lane;
                    const float r0 = rcp_fast(l0), r1 = rcp_fast(l1);
                    const float e0 = fmaf(m0, SCALE_LOG2E, lg2(l0)), e1 = fmaf(m1, SCALE_LOG2E, lg2(l1));
#pragma unroll
                    for (int hb = 0; hb < 4; hb++) {
                        const int h = hb >> 1, b = hb & 1;
                        const float r = h ? r1 : r0;
                        part_store(dst + hb * 32, o[2 * b + h] * r, o[4 + 2 * b + h] * r, o[8 + 2 * b + h] * r, o[12 + 2 * b + h] * r,
                                   h ? e1 : e0, tb + TAG_PART + cur_seq);
                    }
                    if (cur_seq == 7) WSTAMP(pass * 32 + 4);
                }
                if (idx == 0 && cur_seq >= 1) {
                    const uint4* po = g_part + (((cur_seq - 1) & 3) * G + lane) * 128 + (cta & 127);
                    const uint32_t t16 = tb + TAG_PART + cur_seq - 1;
                    const bool last = lane + 128 < G;
                    uint4 v[5];
                    v[4] = make_uint4(0, 0, t16 << 16, __float_as_uint(M_INIT));
                    int it = 0;
                    while (true) {
#pragma unroll
                        for (int k = 0; k < 4; k++) v[k] = pk_load(po + k * 32 * 128);
                        if (last) v[4] = pk_load(po + 128 * 128);
                        bool ok = true;
#pragma unroll
                        for (int k = 0; k < 5; k++) ok = ok && (v[k].z >> 16) == t16;
                        if (__all_sync(0xffffffffu, ok)) break;
                        if (++it > SPIN_LIMIT) __trap();
                    }
                    float gm = M_INIT;
#pragma unroll
                    for (int k = 0; k < 5; k++) gm = fmaxf(gm, __uint_as_float(v[k].w));
                    gm = warp_max(gm);
                    float cw = 0.f, c0 = 0.f, c1 = 0.f, c2 = 0.f, c3 = 0.f;
#pragma unroll
                    for (int k = 0; k < 5; k++) { const float w = ex2(__uint_as_float(v[k].w) - gm); cw += w; part_decode(v[k], w, c0, c1, c2, c3); }
                    warp_sum5(cw, c0, c1, c2, c3);
                    if (lane == 0) {
                        const float rl = rcp_fast(cw);
                        *reinterpret_cast<uint2*>(oc + ((cur_seq - 1) ^ hx) * 2) = make_uint2(pack_bf16(c0 * rl, c1 * rl), pack_bf16(c2 * rl, c3 * rl));
                    }
                    if (cur_seq == 7) WSTAMP(pass * 32 + 5);
                }
#pragma unroll
                for (int i = 0; i < 16; i++) o[i] = 0.f;
                m = M_INIT; l = 0.f;
                cur_seq++;
                res_state = ((cur_seq ^ hx ^ warp) & 1) ? 2 : 0;
            }
            if (!more) break;
            const uint32_t ph = ps & 1;
            float s0, s1;
            mbar_wait(barK, ph);
            uint32_t k, tnext;
            const int pn = take_position(stw, lane, k, tnext);
            const bool nvalid = pn < 2 * NS && lane == 0;
            const int pr = pn >= NS ? 2 * NS - 1 - pn : pn;
            const int nrow = (pr + ((int)__umulhi((uint32_t)pr, hmagic) + 1) * RPH) * 8;
#define JUNK_A 0
#define JUNK_B 0
            const bool keep = ((pn >= NS - KEEP_W) && (pn < NS - KEEP_SKIP) && (pn % KEEP_M < KEEP_N)) ||
                              ((pn >= NS + JUNK_A) && (pn < NS + JUNK_B) && (pr % KEEP_M >= KEEP_N || pn >= NS + KEEP_W));
            const bool demote = (pcur >= NS - KEEP_W) && (pcur < NS - KEEP_SKIP - KEEP_FULL) && (pcur % KEEP_M < KEEP_N);
            const uint32_t doff = (uint32_t)(pcur + (cur_seq + 1) * RPH) * 4096u + lane * 128u;
            if (demote) cp_async4_hint(sb + SM_DUM + lane * 4, reinterpret_cast<const char*>(prm.kc) + doff, pol_first());
            ps = pn * 2 + (ph ^ 1);
            qk_smem(slotK + lmoff, qlane + (cur_seq ^ hx) * 1024, s0, s1);
            if (nvalid) { mbar_expect_tx(barK, 4096); tma_tile(slotK, &tmK, nrow, barK, keep ? pol_normal() : pol_first()); }
            uint32_t P = softmax_step(s0, s1, m, l, o, lane);
            mbar_wait(barV, ph);
            if (demote) cp_async4_hint(sb + SM_DUM + lane * 4, reinterpret_cast<const char*>(prm.vc) + doff, pol_first());
            pv_smem(slotV + lmoff, P, o, lane);
            if (nvalid) { mbar_expect_tx(barV, 4096); tma_tile(slotV, &tmV, nrow, barV, keep ? pol_normal() : pol_first()); }
            take_publish(stw, lane, k, tnext, G);
            __syncwarp();
            if (res_state == 0) res_state = 1;
        }
        __syncwarp();
        if (lane == 0) stw[warp] = ps;
        }
        asm volatile("cp.async.wait_group 0;" ::: "memory");
        __syncthreads();
        TSTAMP(pass * 32 + 6);

        if (cta < 128) {
            PHASE_IDS
            const uint32_t tb = TAG_BASE(pass);
            const uint32_t woa = sb + SM_WO + ((lane & 7) + 8 * (lane >> 4)) * W2_PITCH + (warp < 7 ? warp : 0) * 128 + ((lane >> 3) & 1) * 16;
            const int t = lane & 3;
            float d[4][4];
            uint32_t af[4][4];
            {
                const uint32_t be0 = oc[(pass ? 8 : 0) + t], be1 = oc[(pass ? 12 : 4) + t];
#pragma unroll
                for (int j = 0; j < 4; j++) ldsm4t(af[j], woa + (pass ? 16 * W2_PITCH : 0) + j * 32);
#pragma unroll
                for (int j = 0; j < 4; j++) {
                    d[j][0] = 0.f; d[j][1] = 0.f; d[j][2] = 0.f; d[j][3] = 0.f;
                    mma16816(d[j], af[j], be0, be1);
                }
#pragma unroll
                for (int j = 0; j < 4; j++) ldsm4t(af[j], woa + (pass ? 0 : 16 * W2_PITCH) + j * 32);
            }
            uint32_t bl0 = oc[(pass ? 0 : 8) + t], bl1 = oc[(pass ? 4 : 12) + t];
            TSTAMP(pass * 32 + 7);
            if (warp < MAXG / 32) {
                const uint4 v = pk_poll(g_part + (3 * G + tid) * 128 + cta, tid < G, tb + TAG_PART + 7,
                                        make_uint4(0, 0, 0, __float_as_uint(M_INIT)));
                TSTAMP(pass * 32 + 8);
                const float cm = warp_max(__uint_as_float(v.w));
                float cl = tid < G ? ex2(__uint_as_float(v.w) - cm) : 0.f, c0 = 0.f, c1 = 0.f, c2 = 0.f, c3 = 0.f;
                part_decode(v, cl, c0, c1, c2, c3);
                warp_sum5(cl, c0, c1, c2, c3);
                if (lane == 0) {
                    *reinterpret_cast<float4*>(sc + 32 + warp * 8) = make_float4(c0, c1, cm, cl);
                    *reinterpret_cast<float4*>(sc + 32 + warp * 8 + 4) = make_float4(c2, c3, cm, cl);
                }
            }
            __syncthreads();
            TSTAMP(pass * 32 + 9);
            if (warp < 7) {
                float4 v = make_float4(0.f, 0.f, M_INIT, 0.f);
                if (lane < 4 * (MAXG / 32)) v = *reinterpret_cast<const float4*>(sc + 32 + (lane >> 2) * 8 + (t & 1) * 4);
                float gm = v.z;
#pragma unroll
                for (int of = 4; of <= 16; of <<= 1) gm = fmaxf(gm, __shfl_xor_sync(0xffffffffu, gm, of));
                const float wv = ex2(v.z - gm);
                float cl = v.w * wv, c0 = v.x * wv, c1 = v.y * wv;
#pragma unroll
                for (int of = 4; of <= 16; of <<= 1) {
                    cl += __shfl_xor_sync(0xffffffffu, cl, of);
                    c0 += __shfl_xor_sync(0xffffffffu, c0, of); c1 += __shfl_xor_sync(0xffffffffu, c1, of);
                }
                const float rl = rcp_fast(cl);
                const uint32_t ow = pack_bf16(c0 * rl, c1 * rl);
                if (pass == 0) { if (t >= 2) bl1 = ow; } else { if (t < 2) bl0 = ow; }
                float r0 = 0.f, r1 = 0.f;
#pragma unroll
                for (int j = 0; j < 4; j++) {
                    mma16816(d[j], af[j], bl0, bl1);
                    if (t == j) { r0 = d[j][0]; r1 = d[j][2]; }
                }
                pk_store(RS_DST, __float_as_uint(r0), __float_as_uint(r1), (tb + TAG_R1) << 16, 0);
            }
        }
        TSTAMP(pass * 32 + 10);
        if (cta < NMLP) {
            PHASE_IDS
            const uint32_t tb = TAG_BASE(pass);
            {
                spin_clk(DLY_R);
                const uint4 v = pk_poll(RS_SRC, true, tb + TAG_R1, make_uint4(0, 0, 0, 0));
                float s0 = __uint_as_float(v.x), s1 = __uint_as_float(v.y);
#pragma unroll
                for (int of = 2; of <= 16; of <<= 1) { s0 += __shfl_xor_sync(0xffffffffu, s0, of); s1 += __shfl_xor_sync(0xffffffffu, s1, of); }
                if (lane < 2) *reinterpret_cast<float2*>(sc + 128 + warp * 4 + lane * 2) = make_float2(s0, s1);
                __syncthreads();
                TSTAMP(pass * 32 + 11);
                if (tid == 0) {
                    float4 t = make_float4(0.f, 0.f, 0.f, 0.f);
#pragma unroll
                    for (int w = 0; w < 8; w++) { float4 v = *reinterpret_cast<const float4*>(sc + 128 + w * 4); t.x += v.x; t.y += v.y; t.z += v.z; t.w += v.w; }
                    float4 xo = *reinterpret_cast<const float4*>(xk);
                    xo.x = bf16r(xo.x + bf16r(t.x)); xo.y = bf16r(xo.y + bf16r(t.y)); xo.z = bf16r(xo.z + bf16r(t.z)); xo.w = bf16r(xo.w + bf16r(t.w));
                    pk_store(g_x + cta, pack_bf16(xo.x, xo.y), pack_bf16(xo.z, xo.w), (tb + TAG_X1) << 16, 0);
                    *reinterpret_cast<float4*>(xk) = xo;
                }
            }
            TSTAMP(pass * 32 + 12);
            if (warp < 7) {
                const uint32_t wa = sb + SM_W1 + (warp * 64 + ((lane & 7) >> 1) + 8 * (lane & 1) + 4 * (lane >> 4)) * 32 + ((lane >> 3) & 1) * 16;
                uint32_t af[4][4];
#pragma unroll
                for (int j = 0; j < 4; j++) ldsm4t(af[j], wa + j * 512);
                uint32_t xb[8];
                spin_clk(DLY_X);
                poll_x(warp, lane, tb + TAG_X1, xb);
                TSTAMP(pass * 32 + 13);
                const bool ones = (lane >> 2) == 1;
                float d0[4] = {0.f, 0.f, 0.f, 0.f}, ds[4] = {0.f, 0.f, 0.f, 0.f};
#pragma unroll
                for (int j = 0; j < 4; j++) {
                    uint32_t b0 = ones ? 0x3f803f80u : xb[2 * j], b1 = ones ? 0x3f803f80u : xb[2 * j + 1];
                    uint32_t a2[4] = {0x3f803f80u, xb[2 * j], 0x3f803f80u, xb[2 * j + 1]};
                    mma16816(d0, af[j], b0, b1);
                    mma16816(ds, a2, b0, b1);
                }
                if ((lane & 3) == 0) {
                    const int g = lane >> 2;
                    float2* pp = reinterpret_cast<float2*>(acc) + warp * 16;
                    pp[g] = make_float2(d0[0], d0[1]); pp[g + 8] = make_float2(d0[2], d0[3]);
                    if (lane == 0) *reinterpret_cast<float2*>(sc + 96 + 2 * warp) = make_float2(ds[0], ds[2]);
                }
            }
            __syncthreads();
            TSTAMP(pass * 32 + 14);
            if (warp < 7) {
                uint32_t a2f[4][4];
                const uint32_t w2a = sb + SM_W2 + ((lane & 7) + 8 * (lane >> 4)) * W2_PITCH + warp * 128 + ((lane >> 3) & 1) * 16;
#pragma unroll
                for (int j = 0; j < 4; j++) ldsm4t(a2f[j], w2a + j * 32);
                float mb, rsd;
                ln_stats(sc + 96, mb, rsd);
                float hs = 0.f, ws = 0.f;
#pragma unroll
                for (int w = 0; w < 7; w++) { float2 v = *reinterpret_cast<const float2*>(acc + w * 32 + (lane & 15) * 2); hs += v.x; ws += v.y; }
                float hv = bf16r(bf16r(fmaf(-mb, ws, hs) * rsd) + xk[8 + (lane & 15)]);
                float u = 0.7978845608028654f * fmaf(0.044715f * hv * hv, hv, hv);
                float th = 1.0f - 2.0f * rcp_fast(1.0f + ex2(u * 2.8853900817779268f));
                float gl = 0.5f * hv * (1.0f + th);
                const int t2 = (lane & 3) * 2;
                uint32_t b0 = pack_bf16(__shfl_sync(0xffffffffu, gl, t2), __shfl_sync(0xffffffffu, gl, t2 + 1));
                uint32_t b1 = pack_bf16(__shfl_sync(0xffffffffu, gl, t2 + 8), __shfl_sync(0xffffffffu, gl, t2 + 9));
                float r0 = 0.f, r1 = 0.f;
#pragma unroll
                for (int j = 0; j < 4; j++) {
                    float d[4] = {0.f, 0.f, 0.f, 0.f};
                    mma16816(d, a2f[j], b0, b1);
                    if ((lane & 3) == j) { r0 = d[0]; r1 = d[2]; }
                }
                pk_store(RS_DST, __float_as_uint(r0), __float_as_uint(r1), (tb + TAG_R2) << 16, 0);
            }
            TSTAMP(pass * 32 + 15);
            {
                const int c0 = 16 * (cta >> 2) + (cta & 3);
                spin_clk(DLY_R);
                const uint4 v = pk_poll(RS_SRC, tid < 2 * NMLP, tb + TAG_R2, make_uint4(0, 0, 0, 0));
                float s0 = __uint_as_float(v.x), s1 = __uint_as_float(v.y);
#pragma unroll
                for (int of = 2; of <= 16; of <<= 1) { s0 += __shfl_xor_sync(0xffffffffu, s0, of); s1 += __shfl_xor_sync(0xffffffffu, s1, of); }
                if (lane < 2) *reinterpret_cast<float2*>(sc + 160 + warp * 4 + lane * 2) = make_float2(s0, s1);
                __syncthreads();
                TSTAMP(pass * 32 + 16);
                if (tid == 0) {
                    float4 t = make_float4(0.f, 0.f, 0.f, 0.f);
#pragma unroll
                    for (int w = 0; w < 7; w++) { float4 v = *reinterpret_cast<const float4*>(sc + 160 + w * 4); t.x += v.x; t.y += v.y; t.z += v.z; t.w += v.w; }
                    float4 xo = *reinterpret_cast<const float4*>(xk);
                    const float4 bb = *reinterpret_cast<const float4*>(xk + 4);
                    xo.x = bf16r(xo.x + bf16r(bf16r(t.x) + bb.x)); xo.y = bf16r(xo.y + bf16r(bf16r(t.y) + bb.y));
                    xo.z = bf16r(xo.z + bf16r(bf16r(t.z) + bb.z)); xo.w = bf16r(xo.w + bf16r(bf16r(t.w) + bb.w));
                    if (pass == 0) {
                        pk_store(g_x + cta, pack_bf16(xo.x, xo.y), pack_bf16(xo.z, xo.w), (tb + TAG_X2) << 16, 0);
                        *reinterpret_cast<float4*>(xk) = xo;
                    } else {
                        prm.out[c0] = __float2bfloat16_rn(xo.x); prm.out[c0 + 8] = __float2bfloat16_rn(xo.y);
                        prm.out[c0 + 4] = __float2bfloat16_rn(xo.z); prm.out[c0 + 12] = __float2bfloat16_rn(xo.w);
                        if (cta == 0) {
                            g_ticket[0] = 0;
                            g_epoch[0] = *epw + 1;
                        }
                    }
                }
            }
            TSTAMP(pass * 32 + 17);
        }
    }
}

typedef CUresult (*EncodeFn)(CUtensorMap*, CUtensorMapDataType, cuuint32_t, void*, const cuuint64_t*, const cuuint64_t*,
                             const cuuint32_t*, const cuuint32_t*, CUtensorMapInterleave, CUtensorMapSwizzle,
                             CUtensorMapL2promotion, CUtensorMapFloatOOBfill);

void make_map(EncodeFn fn, CUtensorMap* m, const void* base) {
    cuuint64_t dims[3] = {64, (cuuint64_t)NROWS, 4};
    cuuint64_t strides[2] = {512, 128};
    cuuint32_t box[3] = {64, 8, 4};
    cuuint32_t es[3] = {1, 1, 1};
    fn(m, CU_TENSOR_MAP_DATA_TYPE_BFLOAT16, 3, const_cast<void*>(base), dims, strides, box, es,
       CU_TENSOR_MAP_INTERLEAVE_NONE, CU_TENSOR_MAP_SWIZZLE_128B, CU_TENSOR_MAP_L2_PROMOTION_L2_128B,
       CU_TENSOR_MAP_FLOAT_OOB_FILL_NONE);
}

}

extern "C" void kernel_launch(void* const* d_in, const int* in_sizes, int n_in, void* d_out, int out_size) {
    static EncodeFn fn = nullptr;
    static int nsm = 0;
    if (!fn) {
        cudaDriverEntryPointQueryResult st;
        cudaGetDriverEntryPoint("cuTensorMapEncodeTiled", (void**)&fn, cudaEnableDefault, &st);
        int dev = 0;
        cudaGetDevice(&dev);
        cudaDeviceGetAttribute(&nsm, cudaDevAttrMultiProcessorCount, dev);
        if (nsm > MAXG) nsm = MAXG;
        cudaFuncSetAttribute(fused_kernel, cudaFuncAttributeMaxDynamicSharedMemorySize, SM_TOTAL);
    }
    CUtensorMap tmK, tmV;
    make_map(fn, &tmK, d_in[1]);
    make_map(fn, &tmV, d_in[2]);
    Params p;
    p.x0 = (const __nv_bfloat16*)d_in[0];
    p.kc = (const __nv_bfloat16*)d_in[1];
    p.vc = (const __nv_bfloat16*)d_in[2];
    p.wq = (const __nv_bfloat16*)d_in[3];
    p.wo = (const __nv_bfloat16*)d_in[4];
    p.w1 = (const __nv_bfloat16*)d_in[6];
    p.b1 = (const __nv_bfloat16*)d_in[7];
    p.w2 = (const __nv_bfloat16*)d_in[8];
    p.b2 = (const __nv_bfloat16*)d_in[9];
    p.out = (__nv_bfloat16*)d_out;
    p.hmagic = (uint32_t)((0x100000000ull + (uint64_t)(SK / 8 - nsm * 4) - 1) / (uint64_t)(SK / 8 - nsm * 4));
    fused_kernel<<<nsm, NTHREADS, SM_TOTAL, cudaStreamPerThread>>>(tmK, tmV, p);
}
```

```cpp
#include <cuda_runtime.h>
#include <cuda_bf16.h>
#include <cuda.h>
#include <stdint.h>

namespace {

constexpr int D_MODEL = 448;
constexpr int HKV = 8;
constexpr int SK = 65536;
constexpr int DH = 256;
constexpr int NQ = 4096;
constexpr int FF = 1792;
constexpr int NROWS = HKV * SK;
constexpr int NTHREADS = 256;
constexpr int MAXG = 160;
constexpr int NMLP = 112;

constexpr int KEEP_M = 6;
constexpr int JUNK_M = 54;
constexpr int ALT_START = 2048;
constexpr int TB = 2;
constexpr int TD = 3;

constexpr int W2_PITCH = 912;
constexpr int SM_RING = 0;
constexpr int SM_RES  = 65536;
constexpr int SM_WO   = SM_RES + 131072;
constexpr int SM_QF   = SM_WO + 32 * W2_PITCH;
constexpr int SM_ACC  = SM_QF + 2048;
constexpr int SM_SC   = SM_ACC + 2048;
constexpr int SM_OC   = SM_SC + 1024;
constexpr int SM_ML   = SM_OC + 64;
constexpr int SM_ARR  = SM_ML + 16;
constexpr int SM_EP   = SM_ARR + 64;
constexpr int SM_XK   = SM_EP + 16;
constexpr int SM_ST   = SM_XK + 96;
constexpr int SM_BAR  = SM_ST + 128;
constexpr int SM_CH   = SM_BAR + 8 * 3 * 8;
constexpr int SM_BT   = SM_CH + 64;
constexpr int SM_DUM  = SM_BT + 96;
constexpr int SM_TOTAL = SM_DUM + 128;
static_assert(SM_DUM % 16 == 0, "align");
static_assert(SM_TOTAL <= 232448, "smem");
static_assert(MAXG == 160, "second-level merge is written for 5 warps");

__device__ __align__(128) uint4 g_part[4 * MAXG * 128];
__device__ __align__(128) uint4 g_x[NMLP];
__device__ __align__(128) uint4 g_q[1024];
__device__ __align__(128) unsigned int g_ticket[32];
__device__ __align__(128) unsigned int g_epoch[32];

constexpr int SPIN_LIMIT = 1 << 22;

__device__ __forceinline__ uint32_t smem_u32(const void* p) { return (uint32_t)__cvta_generic_to_shared(p); }
__device__ __forceinline__ void mbar_init(uint32_t bar, uint32_t cnt) {
    asm volatile("mbarrier.init.shared::cta.b64 [%0], %1;" :: "r"(bar), "r"(cnt) : "memory");
}
__device__ __forceinline__ void mbar_expect_tx(uint32_t bar, uint32_t bytes) {
    asm volatile("mbarrier.arrive.expect_tx.shared::cta.b64 _, [%0], %1;" :: "r"(bar), "r"(bytes) : "memory");
}
__device__ __forceinline__ void mbar_arrive(uint32_t bar) {
    asm volatile("mbarrier.arrive.shared::cta.b64 _, [%0];" :: "r"(bar) : "memory");
}
__device__ __forceinline__ void mbar_wait(uint32_t bar, uint32_t parity) {
    uint32_t ok;
    int it = 0;
    do {
        asm volatile("{\n.reg .pred p;\nmbarrier.try_wait.parity.shared::cta.b64 p, [%1], %2;\nselp.u32 %0, 1, 0, p;\n}"
                     : "=r"(ok) : "r"(bar), "r"(parity) : "memory");
        if (++it > SPIN_LIMIT) __trap();
    } while (!ok);
}
__device__ __forceinline__ void tma_tile(uint32_t dst, const CUtensorMap* tm, int row, uint32_t bar, uint64_t pol) {
    asm volatile("cp.async.bulk.tensor.3d.shared::cluster.global.mbarrier::complete_tx::bytes.L2::cache_hint"
                 " [%0], [%1, {%2, %3, %4}], [%5], %6;"
                 :: "r"(dst), "l"(tm), "r"(0), "r"(row), "r"(0), "r"(bar), "l"(pol) : "memory");
}
__device__ __forceinline__ void l2_prefetch(const void* p, uint32_t bytes, uint64_t pol) {
    asm volatile("cp.async.bulk.prefetch.L2.global.L2::cache_hint [%0], %1, %2;" :: "l"(p), "r"(bytes), "l"(pol) : "memory");
}
__device__ __forceinline__ uint64_t pol_first() {
    uint64_t p; asm volatile("createpolicy.fractional.L2::evict_first.b64 %0, 1.0;" : "=l"(p)); return p;
}
__device__ __forceinline__ uint64_t pol_normal() {
    uint64_t p; asm volatile("createpolicy.fractional.L2::evict_normal.b64 %0, 1.0;" : "=l"(p)); return p;
}
__device__ __forceinline__ void cp_async16(uint32_t dst, const void* src) {
    asm volatile("cp.async.cg.shared.global [%0], [%1], 16;" :: "r"(dst), "l"(src) : "memory");
}
__device__ __forceinline__ void cp_async4_hint(uint32_t dst, const void* src, uint64_t pol) {
    asm volatile("cp.async.ca.shared.global.L2::cache_hint [%0], [%1], 4, %2;" :: "r"(dst), "l"(src), "l"(pol) : "memory");
}
__device__ __forceinline__ void ldsm4(uint32_t* r, uint32_t addr) {
    asm volatile("ldmatrix.sync.aligned.m8n8.x4.shared.b16 {%0,%1,%2,%3}, [%4];"
                 : "=r"(r[0]), "=r"(r[1]), "=r"(r[2]), "=r"(r[3]) : "r"(addr) : "memory");
}
__device__ __forceinline__ void ldsm4t(uint32_t* r, uint32_t addr) {
    asm volatile("ldmatrix.sync.aligned.m8n8.x4.trans.shared.b16 {%0,%1,%2,%3}, [%4];"
                 : "=r"(r[0]), "=r"(r[1]), "=r"(r[2]), "=r"(r[3]) : "r"(addr) : "memory");
}
__device__ __forceinline__ uint32_t movtrans(uint32_t a) {
    uint32_t d; asm volatile("movmatrix.sync.aligned.m8n8.trans.b16 %0, %1;" : "=r"(d) : "r"(a)); return d;
}
__device__ __forceinline__ uint4 ldg128(const void* p) {
    uint4 v; asm volatile("ld.global.L1::no_allocate.v4.u32 {%0,%1,%2,%3}, [%4];" : "=r"(v.x), "=r"(v.y), "=r"(v.z), "=r"(v.w) : "l"(p) : "memory"); return v;
}
__device__ __forceinline__ uint2 ldg64(const void* p) {
    uint2 v; asm volatile("ld.global.L1::no_allocate.v2.u32 {%0,%1}, [%2];" : "=r"(v.x), "=r"(v.y) : "l"(p) : "memory"); return v;
}
__device__ __forceinline__ void cta_sync() { asm volatile("bar.sync 0;" ::: "memory"); }
__device__ __forceinline__ void lds128(uint32_t* r, uint32_t addr) {
    asm volatile("ld.volatile.shared.v4.u32 {%0,%1,%2,%3}, [%4];" : "=r"(r[0]), "=r"(r[1]), "=r"(r[2]), "=r"(r[3]) : "r"(addr) : "memory");
}
__device__ __forceinline__ void mma16816(float* c, const uint32_t* a, uint32_t b0, uint32_t b1) {
    asm volatile("mma.sync.aligned.m16n8k16.row.col.f32.bf16.bf16.f32 {%0,%1,%2,%3}, {%4,%5,%6,%7}, {%8,%9}, {%0,%1,%2,%3};"
                 : "+f"(c[0]), "+f"(c[1]), "+f"(c[2]), "+f"(c[3])
                 : "r"(a[0]), "r"(a[1]), "r"(a[2]), "r"(a[3]), "r"(b0), "r"(b1));
}
__device__ __forceinline__ void mma1688(float* c, uint32_t a0, uint32_t a1, uint32_t b0) {
    asm volatile("mma.sync.aligned.m16n8k8.row.col.f32.bf16.bf16.f32 {%0,%1,%2,%3}, {%4,%5}, {%6}, {%0,%1,%2,%3};"
                 : "+f"(c[0]), "+f"(c[1]), "+f"(c[2]), "+f"(c[3])
                 : "r"(a0), "r"(a1), "r"(b0));
}
__device__ __forceinline__ float ex2(float x) { float y; asm("ex2.approx.ftz.f32 %0, %1;" : "=f"(y) : "f"(x)); return y; }
__device__ __forceinline__ float bf16r(float x) {
    uint32_t r; asm("cvt.rn.bf16x2.f32 %0, %1, %2;" : "=r"(r) : "f"(x), "f"(0.f)); return __uint_as_float(r);
}
__device__ __forceinline__ float bf_lo(uint32_t w) { return __uint_as_float(w << 16); }
__device__ __forceinline__ float bf_hi(uint32_t w) { return __uint_as_float(w & 0xffff0000u); }
__device__ __forceinline__ uint32_t pack_bf16(float lo, float hi) {
    uint32_t r; asm("cvt.rn.bf16x2.f32 %0, %1, %2;" : "=r"(r) : "f"(hi), "f"(lo)); return r;
}

__device__ __forceinline__ void pk_store(uint4* p, uint32_t w0, uint32_t w1, uint32_t w2, uint32_t w3) {
    asm volatile("{\n.reg .b128 v;\nmov.b128 v, {%1, %2};\nst.relaxed.gpu.global.b128 [%0], v;\n}"
                 :: "l"(p), "l"(((uint64_t)w1 << 32) | w0), "l"(((uint64_t)w3 << 32) | w2) : "memory");
}
__device__ __forceinline__ uint4 pk_load(const uint4* p) {
    uint64_t a, b;
    asm volatile("{\n.reg .b128 v;\nld.relaxed.gpu.global.b128 v, [%2];\nmov.b128 {%0, %1}, v;\n}" : "=l"(a), "=l"(b) : "l"(p) : "memory");
    return make_uint4((uint32_t)a, (uint32_t)(a >> 32), (uint32_t)b, (uint32_t)(b >> 32));
}
__device__ __forceinline__ uint4 pk_poll(const uint4* p, bool active, uint32_t tag, uint4 v) {
    bool ok = !active;
    int it = 0;
    do {
        if (!ok) { v = pk_load(p); ok = (v.z >> 16) == tag; }
        if (++it > SPIN_LIMIT) __trap();
    } while (!__all_sync(0xffffffffu, ok));
    return v;
}
__device__ __forceinline__ void part_store(uint4* p, float v0, float v1, float v2, float v3, float lse, uint32_t tag) {
    const uint32_t u0 = (__float_as_uint(v0) + 0x800u) >> 12, u1 = (__float_as_uint(v1) + 0x800u) >> 12;
    const uint32_t u2 = (__float_as_uint(v2) + 0x800u) >> 12, u3 = (__float_as_uint(v3) + 0x800u) >> 12;
    pk_store(p, u0 | (u1 << 20), (u1 >> 12) | (u2 << 8) | (u3 << 28), (u3 >> 4) | (tag << 16), __float_as_uint(lse));
}
__device__ __forceinline__ void part_decode(uint4 v, float w, float& c0, float& c1, float& c2, float& c3) {
    c0 = fmaf(w, __uint_as_float(v.x << 12), c0);
    c1 = fmaf(w, __uint_as_float(__funnelshift_r(v.x, v.y, 20) << 12), c1);
    c2 = fmaf(w, __uint_as_float((v.y << 4) & 0xfffff000u), c2);
    c3 = fmaf(w, __uint_as_float(__funnelshift_r(v.y, v.z, 28) << 12), c3);
}
__device__ __forceinline__ float lg2(float x) { float y; asm("lg2.approx.ftz.f32 %0, %1;" : "=f"(y) : "f"(x)); return y; }
__device__ __forceinline__ void spin_clk(uint32_t clk) { uint32_t c0 = clock(); while ((uint32_t)clock() - c0 < clk) {} }
__device__ __forceinline__ uint32_t ticket_fetch(uint32_t n) {
    uint32_t r;
    asm volatile("{\n.reg .u32 l;\n.reg .u64 a;\nmov.u32 l, %%laneid;\nmad.wide.u32 a, l, 4, %1;\natom.relaxed.gpu.global.add.u32 %0, [a], %2;\n}"
                 : "=r"(r) : "l"(&g_ticket[0]), "r"(n) : "memory");
    return r;
}
__device__ __forceinline__ int tid_now() { int t; asm volatile("mov.u32 %0, %%tid.x;" : "=r"(t)); return t; }
__device__ __forceinline__ float rcp_fast(float x) { float y; asm("rcp.approx.ftz.f32 %0, %1;" : "=f"(y) : "f"(x)); return y; }

constexpr float SCALE_LOG2E = 0.0625f * 1.4426950408889634f;
constexpr float M_INIT = -3.0e38f;

struct Params {
    const __nv_bfloat16* x0;
    const __nv_bfloat16* kc;
    const __nv_bfloat16* vc;
    const __nv_bfloat16* wq;
    const __nv_bfloat16* wo;
    const __nv_bfloat16* w1;
    const __nv_bfloat16* b1;
    const __nv_bfloat16* w2;
    const __nv_bfloat16* b2;
    __nv_bfloat16* out;
    uint32_t hmagic;
};

__device__ __forceinline__ uint32_t softmax_step(float s0, float s1, float& m, float& l, float* o, int lane) {
    s0 = bf16r(s0); s1 = bf16r(s1);
    float mx = fmaxf(s0, s1);
    if (__any_sync(0xffffffffu, mx > m)) {
        mx = fmaxf(mx, __shfl_xor_sync(0xffffffffu, mx, 1));
        mx = fmaxf(mx, __shfl_xor_sync(0xffffffffu, mx, 2));
        float mn = fmaxf(m, mx);
        float corr = ex2((m - mn) * SCALE_LOG2E);
        float corr_o = __shfl_xor_sync(0xffffffffu, corr, 4);
        float c0 = (lane & 4) ? corr_o : corr;
        float c1 = (lane & 4) ? corr : corr_o;
        m = mn;
        l *= corr;
#pragma unroll
        for (int i = 0; i < 16; i += 2) { o[i] *= c0; o[i + 1] *= c1; }
    }
    const float p0 = ex2((s0 - m) * SCALE_LOG2E), p1 = ex2((s1 - m) * SCALE_LOG2E);
    l += p0 + p1;
    return pack_bf16(p0, p1);
}

__device__ __forceinline__ void qk_smem(uint32_t a0, uint32_t qaddr, float& s0, float& s1) {
    float e[4] = {0.f, 0.f, 0.f, 0.f}, od[4] = {0.f, 0.f, 0.f, 0.f};
#pragma unroll 1
    for (int c = 0; c < 4; c++) {
        uint32_t b0[4], b1[4], q0[4], q1[4];
        ldsm4(b0, a0);
        lds128(q0, qaddr);
        ldsm4(b1, a0 ^ 64u);
        lds128(q1, qaddr + 128);
        mma16816(e, q0, b0[0], b0[1]);
        mma16816(od, q0, b0[2], b0[3]);
        mma16816(e, q1, b1[0], b1[1]);
        mma16816(od, q1, b1[2], b1[3]);
        a0 += 1024; qaddr += 256;
    }
    s0 = e[0] + od[2]; s1 = e[1] + od[3];
}
__device__ __forceinline__ void pv_smem(uint32_t a0, uint32_t P, float* o, int lane) {
    int gj = lane >> 3;
#pragma unroll 1
    for (int h = 0; h < 2; h++) {
        const uint32_t P0 = gj == 0 ? P : 0u, P1 = gj == 1 ? P : 0u;
        uint32_t a[4][4];
#pragma unroll
        for (int i = 0; i < 4; i++) ldsm4t(a[i], a0 + i * 1024);
#pragma unroll
        for (int i = 0; i < 4; i++) mma1688(o + 4 * i, a[i][0], a[i][1], P0);
#pragma unroll
        for (int i = 0; i < 4; i++) mma1688(o + 4 * i, a[i][2], a[i][3], P1);
        a0 ^= 64u; gj -= 2;
    }
}

constexpr uint32_t PK_FAIL = 0xff;
template <int J>
__device__ __forceinline__ void mov_if(uint32_t& dst, uint32_t src, int sel) {
    asm volatile("{\n.reg .pred p;\nsetp.eq.s32 p, %2, %3;\n@p mov.b32 %0, %1;\n}" : "+r"(dst) : "r"(src), "r"(sel), "n"(J));
}
template <int J> __device__ __forceinline__ void pk_put(uint32_t* dst, const uint32_t* P, int h) {
#pragma unroll
    for (int i = 0; i < 26; i++) mov_if<J>(dst[i], P[i], h);
}
template <int J> __device__ __forceinline__ void pk_get(const uint32_t* src, uint32_t* L, uint32_t* N, uint32_t& S, int sel) {
#pragma unroll
    for (int i = 0; i < 8; i++) { mov_if<2 * J>(L[i], src[i], sel); mov_if<2 * J + 1>(L[i], src[8 + i], sel); }
#pragma unroll
    for (int i = 0; i < 4; i++) { mov_if<2 * J>(N[i], src[16 + i], sel); mov_if<2 * J + 1>(N[i], src[20 + i], sel); }
    mov_if<2 * J>(S, src[24], sel); mov_if<2 * J + 1>(S, src[25], sel);
}
__device__ __forceinline__ uint32_t pack13(const uint32_t* f, uint32_t* P) {
    uint32_t mx = 0;
#pragma unroll
    for (int i = 0; i < 32; i++) mx = __vmaxu2(mx, f[i] & 0x7fff7fffu);
    const uint32_t emax = __reduce_max_sync(0xffffffffu, max(mx & 0xffffu, mx >> 16)) >> 8;
    const uint32_t base = emax > 15 ? emax - 15 : 0;
    uint32_t bad = 0;
    P[24] = 0; P[25] = 0;
#pragma unroll
    for (int k = 0; k < 16; k++) {
        P[k] = __byte_perm(f[2 * k], f[2 * k + 1], 0x6420);
        const uint32_t H = __byte_perm(f[2 * k], f[2 * k + 1], 0x7531);
        const uint32_t nz = (((H & 0x7f7f7f7fu) + 0x7f7f7f7fu) >> 7) & 0x01010101u;
        const uint32_t T = (H | 0x80808080u) - nz * base;
        bad |= (T & 0x70707070u) | (~(T - nz) & 0x80808080u);
        if (k & 1) P[16 + (k >> 1)] |= (T & 0x0f0f0f0fu) << 4; else P[16 + (k >> 1)] = T & 0x0f0f0f0fu;
        P[24 + (k >> 3)] |= ((H >> 7) & 0x01010101u) << (k & 7);
    }
    return __any_sync(0xffffffffu, bad != 0) ? PK_FAIL : base;
}
template <int K>
__device__ __forceinline__ void unpack13(uint32_t L, uint32_t N, uint32_t S, uint32_t base, uint32_t& f0, uint32_t& f1) {
    const uint32_t nib = ((K & 1) ? N >> 4 : N) & 0x0f0f0f0fu;
    const uint32_t nz = ((nib + 0x0f0f0f0fu) >> 4) & 0x01010101u;
    const uint32_t H = (nz * base + nib) | ((S << (7 - K)) & 0x80808080u);
    f0 = __byte_perm(L, H, 0x5140); f1 = __byte_perm(L, H, 0x7362);
}
__device__ __forceinline__ void qk_half(const uint32_t* L, const uint32_t* N, uint32_t S, uint32_t base, uint32_t qaddr, float* e, float* od) {
    uint32_t a[4], b0, b1;
    lds128(a, qaddr);       unpack13<0>(L[0], N[0], S, base, b0, b1); mma16816(e, a, b0, b1); unpack13<1>(L[1], N[0], S, base, b0, b1); mma16816(od, a, b0, b1);
    lds128(a, qaddr + 128); unpack13<2>(L[2], N[1], S, base, b0, b1); mma16816(e, a, b0, b1); unpack13<3>(L[3], N[1], S, base, b0, b1); mma16816(od, a, b0, b1);
    lds128(a, qaddr + 256); unpack13<4>(L[4], N[2], S, base, b0, b1); mma16816(e, a, b0, b1); unpack13<5>(L[5], N[2], S, base, b0, b1); mma16816(od, a, b0, b1);
    lds128(a, qaddr + 384); unpack13<6>(L[6], N[3], S, base, b0, b1); mma16816(e, a, b0, b1); unpack13<7>(L[7], N[3], S, base, b0, b1); mma16816(od, a, b0, b1);
}
__device__ __forceinline__ void pv_half(const uint32_t* L, const uint32_t* N, uint32_t S, uint32_t base, uint32_t P0, uint32_t P1, float* o) {
    uint32_t a0, a1;
    unpack13<0>(L[0], N[0], S, base, a0, a1); mma1688(o, a0, a1, P0);      unpack13<1>(L[1], N[0], S, base, a0, a1); mma1688(o, a0, a1, P1);
    unpack13<2>(L[2], N[1], S, base, a0, a1); mma1688(o + 4, a0, a1, P0);  unpack13<3>(L[3], N[1], S, base, a0, a1); mma1688(o + 4, a0, a1, P1);
    unpack13<4>(L[4], N[2], S, base, a0, a1); mma1688(o + 8, a0, a1, P0);  unpack13<5>(L[5], N[2], S, base, a0, a1); mma1688(o + 8, a0, a1, P1);
    unpack13<6>(L[6], N[3], S, base, a0, a1); mma1688(o + 12, a0, a1, P0); unpack13<7>(L[7], N[3], S, base, a0, a1); mma1688(o + 12, a0, a1, P1);
}
__device__ __forceinline__ void pks_store(unsigned char* lp, const uint32_t* P) {
#pragma unroll
    for (int j = 0; j < 6; j++) *reinterpret_cast<uint4*>(lp + j * 512) = make_uint4(P[4 * j], P[4 * j + 1], P[4 * j + 2], P[4 * j + 3]);
}
__device__ __forceinline__ void qk_glob(const uint32_t* gp, uint32_t qaddr, float& s0, float& s1) {
    float e[4] = {0.f, 0.f, 0.f, 0.f}, od[4] = {0.f, 0.f, 0.f, 0.f};
#pragma unroll 1
    for (int n = 0; n < 8; n++) {
        uint32_t a[4];
        lds128(a, qaddr + n * 128);
        mma16816(e, a, gp[n * 16], gp[n * 16 + 4]);
        mma16816(od, a, gp[n * 16 + 8], gp[n * 16 + 12]);
    }
    s0 = e[0] + od[2]; s1 = e[1] + od[3];
}
__device__ __forceinline__ void pv_glob(const uint32_t* gp, uint32_t Pf, float* o, int lane) {
#pragma unroll 1
    for (int j = 0; j < 4; j++) {
        const uint32_t Pj = (lane >> 3) == j ? Pf : 0u;
#pragma unroll
        for (int i = 0; i < 4; i++) mma1688(o + 4 * i, movtrans(gp[i * 32 + j * 8]), movtrans(gp[i * 32 + j * 8 + 4]), Pj);
    }
}

__device__ __forceinline__ float2 ln_partial(float s, float q) { return make_float2(s, fmaf(-s * (1.0f / 64), s, q)); }
__device__ __forceinline__ void ln_stats(const float* st, float& mb, float& rsd) {
    const float4 v0 = *reinterpret_cast<const float4*>(st), v1 = *reinterpret_cast<const float4*>(st + 4);
    const float4 v2 = *reinterpret_cast<const float4*>(st + 8);
    const float2 v3 = *reinterpret_cast<const float2*>(st + 12);
    const float sm = (((v0.x + v0.z) + (v1.x + v1.z)) + ((v2.x + v2.z) + v3.x)) * (1.0f / 7);
    const float m2 = ((v0.y + v0.w) + (v1.y + v1.w)) + ((v2.y + v2.w) + v3.y);
    const float d0 = v0.x - sm, d1 = v0.z - sm, d2 = v1.x - sm, d3 = v1.z - sm, d4 = v2.x - sm, d5 = v2.z - sm, d6 = v3.x - sm;
    const float dd = (fmaf(d0, d0, d1 * d1) + fmaf(d2, d2, d3 * d3)) + (fmaf(d4, d4, d5 * d5) + d6 * d6);
    const float var = fmaf(dd, 1.0f / 64, m2) * (1.0f / D_MODEL);
    mb = bf16r(sm * (1.0f / 64));
    float sd; asm("sqrt.approx.ftz.f32 %0, %1;" : "=f"(sd) : "f"(bf16r(bf16r(fmaxf(var, 0.f)) + 1e-5f)));
    rsd = rcp_fast(bf16r(sd));
}

__device__ __forceinline__ float warp_max(float v) {
    int i = __float_as_int(v);
    i ^= (i >> 31) & 0x7fffffff;
    i = __reduce_max_sync(0xffffffffu, i);
    i ^= (i >> 31) & 0x7fffffff;
    return __int_as_float(i);
}
__device__ __forceinline__ void warp_sum5(float& a, float& b, float& c, float& d, float& e) {
#pragma unroll
    for (int of = 16; of; of >>= 1) {
        a += __shfl_xor_sync(0xffffffffu, a, of); b += __shfl_xor_sync(0xffffffffu, b, of);
        c += __shfl_xor_sync(0xffffffffu, c, of); d += __shfl_xor_sync(0xffffffffu, d, of);
        e += __shfl_xor_sync(0xffffffffu, e, of);
    }
}

template <int NL>
__device__ __forceinline__ void reduce_packets(const uint4* src, uint32_t tag, float& s0, float& s1) {
    uint4 v[NL];
    int it = 0;
    while (true) {
        bool ok = true;
#pragma unroll
        for (int k = 0; k < NL; k++) v[k] = pk_load(src + k * 32);
#pragma unroll
        for (int k = 0; k < NL; k++) ok = ok && (v[k].z >> 16) == tag;
        if (__all_sync(0xffffffffu, ok)) break;
        if (++it > SPIN_LIMIT) __trap();
    }
    float a[4], b[4];
#pragma unroll
    for (int k = 0; k < 4; k++) {
        a[k] = __uint_as_float(v[k].x); b[k] = __uint_as_float(v[k].y);
        if (k + 4 < NL) { a[k] += __uint_as_float(v[k + 4].x); b[k] += __uint_as_float(v[k + 4].y); }
    }
    s0 = (a[0] + a[1]) + (a[2] + a[3]); s1 = (b[0] + b[1]) + (b[2] + b[3]);
#pragma unroll
    for (int of = 2; of <= 16; of <<= 1) { s0 += __shfl_xor_sync(0xffffffffu, s0, of); s1 += __shfl_xor_sync(0xffffffffu, s1, of); }
}
__device__ __forceinline__ void lazy_wait(const uint4* p, uint32_t tag) {
    if ((threadIdx.x & 31) == 0) {
        int it = 0;
        while ((pk_load(p).z >> 16) != tag) { __nanosleep(100); if (++it > SPIN_LIMIT) __trap(); }
    }
    __syncwarp();
}

#define KROW(s_) (4 * ((s_) >> 2) + (((s_) >> 1) & 1) + 8 * ((s_) & 1))
#define W1_SRC(j_) (prm.w1 + (size_t)(warp * 64 + KROW(lane >> 2) + ((j_) >> 1) * 16 + ((j_) & 1) * 2) * FF + cta * 16 + (lane & 3) * 4)
#define W2_SRC(j_) (prm.w2 + (size_t)(cta * 16 + (lane >> 2) + ((j_) & 1) * 8) * D_MODEL + warp * 64 + (lane & 3) * 8 + ((j_) >> 1) * 32)
__device__ __forceinline__ void q_store(unsigned char* slot, int i, uint4 v) {
    const int h = i >> 6, d = (i & 63) * 4;
    const int quarter = (d >> 3) & 3, t = (d & 7) >> 1;
    uint32_t* dst = reinterpret_cast<uint32_t*>(slot + (d >> 5) * 128 + (h * 4 + t) * 16 + (((quarter & 1) << 1) | (quarter >> 1)) * 4);
    dst[0] = v.x; dst[4] = v.y;
}
#define RS_SRC (g_part + cta * 256 + lane)
#define TAG_BASE(pass_) ((*epw * 32 + (pass_) * 16) & 0xffffu)
constexpr uint32_t TAG_PART = 1, TAG_R1 = 9, TAG_X1 = 10, TAG_R2 = 11, TAG_X2 = 12, TAG_Q = 13;
constexpr uint32_t DLY_R1 = 700, DLY_R2 = 900, DLY_X = 300, DLY_Q = 300;

__device__ __forceinline__ int take_position(volatile uint32_t* stw, int lane, uint32_t& k, uint32_t& tnext) {
    k = 0;
    if (lane == 0) k = atomicAdd(const_cast<uint32_t*>(stw) + 24, 1u);
    k = __shfl_sync(0xffffffffu, k, 0);
    tnext = 0;
    const uint32_t b = k / TB;
    int it = 0;
    if (k % TB == 0) {
        while (!__all_sync(0xffffffffu, stw[25] == b)) { if (++it > SPIN_LIMIT) __trap(); }
        if (lane == 0) { tnext = ticket_fetch(TB); stw[25] = b + 1; }
    }
    uint32_t w;
    while (((w = stw[8 + (b & 15)]) & 0xfffu) != (b >> 4)) { if (++it > SPIN_LIMIT) __trap(); }
    return (int)(w >> 12) + (int)(k % TB);
}
__device__ __forceinline__ void take_publish(volatile uint32_t* stw, int lane, uint32_t k, uint32_t tnext, int G) {
    if (lane == 0 && k % TB == 0) {
        const uint32_t b = k / TB + TD;
        stw[8 + (b & 15)] = ((tnext + G * (TB * TD)) << 12) | (b >> 4);
    }
}

#define GAP_PREFETCH(b_) do { if (tid_now() == 224) { \
        const int pr_ = NS - 1 - ((b_) * G + cta); \
        const size_t off_ = (size_t)(pr_ + ((int)__umulhi((uint32_t)pr_, hmagic) + 1) * RPH) * 4096; \
        l2_prefetch(reinterpret_cast<const char*>(prm.kc) + off_, 4096, pol_first()); \
        l2_prefetch(reinterpret_cast<const char*>(prm.vc) + off_, 4096, pol_first()); \
    } } while (0)

#define ALT_POS(p_) (((p_) >= ALT_START && (p_) < NS) || (p_) >= NS + ALT_START)
#define KEEP_POS(p_) ((p_) < NS && (uint32_t)(p_) % KEEP_M == 0)
#define RES_HEAD(i_) (((warp & 6) + 2 + (i_)) & 7)
#define RES_ROW(h_) ((h_) * SK + (cta * 6 + ((warp - ((h_) & 6) - 2) & 7)) * 8)
#define PHASE_IDS const int tid = tid_now(), warp = __shfl_sync(0xffffffffu, tid >> 5, 0), lane = tid & 31; (void)warp; (void)lane;
#define RING_IDS \
    const uint32_t barK = sb + SM_BAR + warp * 24, barV = barK + 8, barR = barK + 16; (void)barV; (void)barR; \
    const uint32_t slotK = sb + SM_RING + warp * 8192, slotV = slotK + 4096; (void)slotV; \
    const uint32_t lmoff = (lane & 7) * 128 + ((((lane >> 3) ^ lane) & 7) << 4); (void)lmoff;

__global__ void __launch_bounds__(NTHREADS, 1)
fused_kernel(const __grid_constant__ CUtensorMap tmK, const __grid_constant__ CUtensorMap tmV, const Params prm) {
    if ((threadIdx.x & 31) == 0 && blockIdx.x < 128)
        l2_prefetch(reinterpret_cast<const char*>(prm.wq) + blockIdx.x * 28672 + (threadIdx.x >> 5) * 3584, 3584, pol_normal());
    extern __shared__ __align__(1024) unsigned char smem_dyn[];
    constexpr uint32_t sb = 1024;
    if (smem_u32(smem_dyn) != sb) __trap();
    unsigned char* const smem = reinterpret_cast<unsigned char*>(__cvta_shared_to_generic(sb));
    const int cta = blockIdx.x, G = gridDim.x;
    const int RPH = G * 6;
    const int NS = 8 * (SK / 8 - RPH) - 8 * G;
    const uint32_t hmagic = prm.hmagic;
    volatile uint32_t* const stw = reinterpret_cast<volatile uint32_t*>(smem + SM_ST);
    volatile uint32_t* const epw = reinterpret_cast<volatile uint32_t*>(smem + SM_EP);
    float* const acc = reinterpret_cast<float*>(smem + SM_ACC);
    float* const sc = reinterpret_cast<float*>(smem + SM_SC);
    uint32_t* const oc = reinterpret_cast<uint32_t*>(smem + SM_OC);
    float* const accml = reinterpret_cast<float*>(smem + SM_ML);
    float* const xk = reinterpret_cast<float*>(smem + SM_XK);

#define RES_LOAD(i_) do { \
        tma_tile(sb + SM_RES + warp * 16384 + ((i_) - 4) * 8192, &tmK, RES_ROW(RES_HEAD(i_)), barR, pol_first()); \
        tma_tile(sb + SM_RES + warp * 16384 + ((i_) - 4) * 8192 + 4096, &tmV, RES_ROW(RES_HEAD(i_)), barR, pol_first()); \
    } while (0)
#define START_LOADS do { if (lane == 0) { \
        RING_IDS \
        const uint64_t pf = pol_first(); \
        mbar_expect_tx(barK, 4096); tma_tile(slotK, &tmK, RES_ROW(RES_HEAD(0)), barK, pf); \
        mbar_expect_tx(barV, 4096); tma_tile(slotV, &tmV, RES_ROW(RES_HEAD(0)), barV, pf); \
        mbar_expect_tx(barR, 8192); RES_LOAD(5); \
    } __syncwarp(); } while (0)
    {
    PHASE_IDS
    if (lane == 0) {
        RING_IDS
        mbar_init(barK, 1); mbar_init(barV, 1); mbar_init(barR, 1); mbar_init(sb + SM_CH + warp * 8, 1);
        asm volatile("fence.mbarrier_init.release.cluster;" ::: "memory");
        asm volatile("fence.proxy.async.shared::cta;" ::: "memory");
    }
    if (warp == 7) {
        uint32_t sv = 0;
        if (cta < NMLP && lane < 24) {
            const int c = 16 * (cta >> 2) + 4 * ((cta >> 1) & 1) + (cta & 1) + 2 * ((lane >> 1) & 1) + 8 * (lane & 1);
            sv = *reinterpret_cast<const volatile unsigned short*>(lane < 4 ? prm.x0 + c : lane < 8 ? prm.b2 + c : prm.b1 + cta * 16 + lane - 8);
        }
        if (lane == 31) sv = *reinterpret_cast<volatile unsigned int*>(&g_epoch[0]);
        START_LOADS;
        if (lane < 16) {
            reinterpret_cast<unsigned int*>(smem + SM_ARR)[lane] = 0;
            stw[8 + lane] = lane < TD ? (uint32_t)((cta * TD + lane) * TB) << 12 : 0xfffu;
        }
        if (lane == 16) { stw[24] = 0; stw[25] = 0; mbar_init(sb + SM_EP + 8, 1); }
        if (lane < 24) xk[lane] = __uint_as_float(sv << 16);
        if (lane == 31) *epw = sv;
    } else if (cta >= 128) {
        START_LOADS;
    }
    }

#define GATHER_Q do { \
        const uint32_t tq = TAG_BASE(pass) + TAG_Q; \
        const uint4* src = g_q + ((tid >> 7) ^ 7) * 128 + (tid & 127); \
        if (cta >= 128) lazy_wait(src, tq); \
        else spin_clk(DLY_Q); \
        q_store(smem + SM_QF + (tid >> 7) * 1024, tid & 127, pk_poll(src, true, tq, make_uint4(0, 0, 0, 0))); \
        __syncthreads(); \
    } while (0)
#define PK_FETCH(h_, c_) do { \
        if ((h_) >= 7) { \
            const uint32_t la = sb + SM_RES + warp * 16384 + ((h_) - 7) * 3072 + lane * 16; \
            lds128(L, la + (c_) * 1024); lds128(L + 4, la + (c_) * 1024 + 512); lds128(N, la + 2048 + (c_) * 512); \
            S = (c_) ? rs1 : rs0; \
            if ((h_) > 7) S = *reinterpret_cast<const uint32_t*>(smem + SM_RES + warp * 16384 + 15360 + ((h_) - 8) * 256 + lane * 8 + (c_) * 4); \
        } else { \
            const int sel = 2 * (h_) + (c_); \
            pk_get<PK_J0>(rp[PK_J0], L, N, S, sel); pk_get<PK_J0 + 2>(rp[PK_J0 + 2], L, N, S, sel); pk_get<PK_J0 + 4>(rp[PK_J0 + 4], L, N, S, sel); \
            if (PK_J0 == 0) pk_get<6>(rp[6], L, N, S, sel); \
        } \
    } while (0)
    uint32_t rp[7][26] = {}, rs0 = 0, rs1 = 0;

#pragma unroll 1
    for (int pass = 0; pass < 2; pass++) {
        if (cta < 128) {
            PHASE_IDS
            if (warp < 7) {
                uint32_t af[8][4];
                {
                    const __nv_bfloat16* wp = prm.wq + (size_t)(warp * 64 + KROW(lane >> 2)) * NQ + (cta ^ 64) * 32 + (lane & 3) * 8;
#pragma unroll
                    for (int j = 0; j < 8; j++) {
                        const uint4 v = ldg128(wp + (size_t)((j >> 1) * 16 + (j & 1) * 2) * NQ);
                        af[j][0] = v.x; af[j][1] = v.y; af[j][2] = v.z; af[j][3] = v.w;
                    }
                }
                uint32_t xa = 0, xb = 0, xc = 0, xd = 0;
                if (pass == 0 && lane < 16) {
                    const volatile unsigned short* xp = reinterpret_cast<const volatile unsigned short*>(prm.x0) + warp * 64 + (lane >> 2) * 16 + 4 * ((lane >> 1) & 1) + (lane & 1);
                    xa = xp[0]; xb = xp[2]; xc = xp[8]; xd = xp[10];
                }
                if (pass == 0) START_LOADS;
                xa |= xc << 16; xb |= xd << 16;
#pragma unroll
                for (int j = 0; j < 8; j++) {
#pragma unroll
                    for (int r = 0; r < 4; r++) af[j][r] = movtrans(af[j][r]);
                }
                if (pass == 1) {
                    const uint32_t tx = TAG_BASE(0) + TAG_X2;
                    cta_sync();
                    if (cta < NMLP) spin_clk(DLY_X);
                    const uint4 v = pk_poll(g_x + warp * 16 + lane, lane < 16, tx, make_uint4(0, 0, 0, 0));
                    xa = v.x; xb = v.y;
                }
                {
                    float ds[4] = {0.f, 0.f, 0.f, 0.f}, dt[4] = {0.f, 0.f, 0.f, 0.f};
#pragma unroll
                    for (int j = 0; j < 4; j++) {
                        const uint32_t x0 = __shfl_sync(0xffffffffu, xa, j * 4 + (lane & 3)), x1 = __shfl_sync(0xffffffffu, xb, j * 4 + (lane & 3));
                        const uint32_t a2[4] = {0x3f803f80u, x0, 0x3f803f80u, x1};
                        mma16816((j & 1) ? dt : ds, a2, x0, x1);
                    }
                    if (lane == 0) *reinterpret_cast<float2*>(sc + 2 * warp) = ln_partial(ds[0] + dt[0], ds[2] + dt[2]);
                }
                cta_sync();
                float mb, rsd;
                ln_stats(sc, mb, rsd);
                xa = pack_bf16(bf16r(bf_lo(xa) - mb) * rsd, bf16r(bf_hi(xa) - mb) * rsd);
                xb = pack_bf16(bf16r(bf_lo(xb) - mb) * rsd, bf16r(bf_hi(xb) - mb) * rsd);
                float d0[4] = {0.f, 0.f, 0.f, 0.f}, d1[4] = {0.f, 0.f, 0.f, 0.f}, d2[4] = {0.f, 0.f, 0.f, 0.f}, d3[4] = {0.f, 0.f, 0.f, 0.f};
#pragma unroll
                for (int j = 0; j < 4; j++) {
                    const uint32_t b0 = __shfl_sync(0xffffffffu, xa, j * 4 + (lane & 3)), b1 = __shfl_sync(0xffffffffu, xb, j * 4 + (lane & 3));
                    const uint32_t a0[4] = {af[2 * j][0], af[2 * j][1], af[2 * j + 1][0], af[2 * j + 1][1]};
                    const uint32_t a1[4] = {af[2 * j][2], af[2 * j][3], af[2 * j + 1][2], af[2 * j + 1][3]};
                    mma16816((j & 1) ? d2 : d0, a0, b0, b1);
                    mma16816((j & 1) ? d3 : d1, a1, b0, b1);
                }
                if ((lane & 3) == 0) {
                    const int g = lane >> 2;
                    float* pp = acc + warp * 32 + 8 * (g >> 1) + (g & 1);
                    pp[0] = d0[0] + d2[0]; pp[2] = d0[2] + d2[2]; pp[4] = d1[0] + d3[0]; pp[6] = d1[2] + d3[2];
                }
            } else {
                if (pass == 1) {
                    if (cta >= NMLP) lazy_wait(g_x + (cta - NMLP), TAG_BASE(0) + TAG_X2);
                    cta_sync();
                }
                cta_sync();
            }
            __syncthreads();
            if (warp == 0) {
                float v[7];
#pragma unroll
                for (int w = 0; w < 7; w++) v[w] = acc[w * 32 + lane];
                const float qv = ((v[0] + v[1]) + (v[2] + v[3])) + ((v[4] + v[5]) + v[6]);
                const uint32_t pr = pack_bf16(qv, __shfl_down_sync(0xffffffffu, qv, 1));
                const uint32_t pr2 = __shfl_down_sync(0xffffffffu, pr, 2);
                if ((lane & 3) == 0) pk_store(g_q + (cta ^ 64) * 8 + (lane >> 2), pr, pr2, (TAG_BASE(pass) + TAG_Q) << 16, 0);
            }
        } else if (pass == 0) {
            __syncthreads();
        }
        if (pass == 1) GAP_PREFETCH(3);
        if (pass == 0) {
            PHASE_IDS
            RING_IDS
            if (cta < 128) {
                const int h = cta >> 6, b = (cta >> 5) & 1, cl = cta & 31;
                const int dbase = h * 256 + 16 * (cl & 3) + (cl >> 2) + 8 * b;
#pragma unroll
                for (int k = 0; k < 7; k++) {
                    int c = tid + k * 256;
                    int lr = c / 56, cc = c - lr * 56;
                    int grow = (lr >> 2) * 512 + (lr & 3) * 64 + dbase;
                    cp_async16(sb + SM_WO + lr * W2_PITCH + cc * 16, prm.wo + (size_t)grow * D_MODEL + cc * 8);
                }
            }
            asm volatile("cp.async.commit_group;" ::: "memory");
            int nrow = 0;
            bool valt = false;
#pragma unroll 1
            for (int st = 0; st < 12; st++) {
                const int h = (int)((0x768954AB3210ull >> (4 * st)) & 15);
                const bool ring = h < 8;
                const uint32_t src = ring ? slotK + (h & 1) * 4096 : sb + SM_RES + warp * 16384 + (h - 8) * 4096;
                if (h == 6) {
                    uint32_t k, tnext;
                    const int p0 = take_position(stw, lane, k, tnext);
                    nrow = (p0 + ((int)__umulhi((uint32_t)p0, hmagic) + 1) * RPH) * 8;
                    valt = ALT_POS(p0);
                    if (p0 >= NS) __trap();
                    if (lane == 0) stw[warp] = p0 * 8 + (valt ? 4 : 0);
                    take_publish(stw, lane, k, tnext, G);
                } else if (h < 6) {
                    nrow = RES_ROW(RES_HEAD((h >> 1) + 1));
                }
                if (ring || (h & 1)) mbar_wait(ring ? barK + (h & 1) * 8 : barR, ring ? (h >> 1) & 1 : h < 10);
                uint32_t f[32];
                if (h & 1) {
#pragma unroll
                    for (int n = 0; n < 8; n++) ldsm4t(&f[4 * n], src + ((n >> 2) ? (lmoff ^ 64u) : lmoff) + (n & 3) * 1024);
                } else {
#pragma unroll
                    for (int n = 0; n < 8; n++) ldsm4(&f[4 * n], src + ((n & 1) ? (lmoff ^ 64u) : lmoff) + (n >> 1) * 1024);
                }
                __syncwarp();
                if (lane == 0) {
                    if (ring && !((h & 1) && valt)) {
                        mbar_expect_tx(barK + (h & 1) * 8, 4096);
                        tma_tile(src, (h & 1) ? &tmV : &tmK, nrow, barK + (h & 1) * 8, pol_first());
                    }
                    if (h == 11) { mbar_expect_tx(barR, 8192); RES_LOAD(4); }
                }
                uint32_t P[26];
                smem[SM_BT + warp * 12 + h] = (unsigned char)pack13(f, P);
                if (h >= 7) {
                    pks_store(smem + SM_RES + warp * 16384 + (h - 7) * 3072 + lane * 16, P);
                    if (h == 7) { rs0 = P[24]; rs1 = P[25]; }
                    else *reinterpret_cast<uint2*>(smem + SM_RES + warp * 16384 + 15360 + (h - 8) * 256 + lane * 8) = make_uint2(P[24], P[25]);
                    __syncwarp();
                } else {
                    pk_put<0>(rp[0], P, h); pk_put<1>(rp[1], P, h); pk_put<2>(rp[2], P, h); pk_put<3>(rp[3], P, h);
                    pk_put<4>(rp[4], P, h); pk_put<5>(rp[5], P, h); pk_put<6>(rp[6], P, h);
                }
                if (st == 1 && warp == 7) {
                    const uint32_t tq = TAG_BASE(0) + TAG_Q;
#pragma unroll 1
                    for (int hh = 0; hh < 2; hh++) {
                        uint4 v[4];
                        int it = 0;
                        while (true) {
                            bool ok = true;
#pragma unroll
                            for (int k = 0; k < 4; k++) v[k] = pk_load(g_q + hh * 128 + k * 32 + lane);
#pragma unroll
                            for (int k = 0; k < 4; k++) ok = ok && (v[k].z >> 16) == tq;
                            if (__all_sync(0xffffffffu, ok)) break;
                            if (++it > SPIN_LIMIT) __trap();
                        }
#pragma unroll
                        for (int k = 0; k < 4; k++) q_store(smem + SM_QF + hh * 1024, lane + k * 32, v[k]);
                    }
                    __syncwarp();
                    if (lane == 0) mbar_arrive(sb + SM_EP + 8);
                }
            }
            mbar_wait(sb + SM_EP + 8, 0);
        }
        else {
            PHASE_IDS
            GATHER_Q;
        }

        const int hx = pass ? 7 : 0;
        {
        PHASE_IDS
        RING_IDS
        const uint32_t qlane = sb + SM_QF + (((lane >> 2) & 1) * 4 + (lane & 3)) * 16;
        int ps = stw[warp];
        bool fin = false;
        float o[16];
#pragma unroll
        for (int i = 0; i < 16; i++) o[i] = 0.f;
        float m = M_INIT, l = 0.f;
        int cur_seq = 0;
        int res_state = ((hx ^ warp) & 6) ? 0 : 2;
#pragma unroll 1
        while (true) {
            const int pcur = ps >> 3;
            const bool rsv = ps & 2;
            const bool more = !fin && pcur < 2 * NS;
            const int seq = more ? (rsv ? 7 : (int)__umulhi((uint32_t)(pass ? 2 * NS - 1 - pcur : pcur), hmagic)) ^ hx : 8;
#pragma unroll 1
            while (true) {
                if (res_state == 1 || (res_state == 0 && cur_seq < seq)) {
                    res_state = 2;
                    const int head = cur_seq ^ hx;
                    const uint32_t qa = qlane + (cur_seq & 1) * 1024;
                    const int ti = (head - (warp & 6) - 2) & 7;
                    const uint32_t bK = smem[SM_BT + warp * 12 + 2 * ti], bV = smem[SM_BT + warp * 12 + 2 * ti + 1];
                    const size_t go = (size_t)(RES_ROW(head) + (lane >> 2)) * 128 + (lane & 3);
                    float s0, s1;
                    if (bK == PK_FAIL) qk_glob(reinterpret_cast<const uint32_t*>(prm.kc) + go, qa, s0, s1);
                    else {
                        float e[4] = {0.f, 0.f, 0.f, 0.f}, od[4] = {0.f, 0.f, 0.f, 0.f};
#pragma unroll 1
                        for (int c = 0; c < 2; c++) {
                            uint32_t L[8] = {}, N[4] = {}, S = 0;
                            constexpr int PK_J0 = 0;
                            PK_FETCH(2 * ti, c);
                            qk_half(L, N, S, bK, qa + c * 512, e, od);
                        }
                        s0 = e[0] + od[2]; s1 = e[1] + od[3];
                    }
                    const uint32_t Pf = softmax_step(s0, s1, m, l, o, lane);
                    if (bV == PK_FAIL) pv_glob(reinterpret_cast<const uint32_t*>(prm.vc) + go, Pf, o, lane);
                    else {
#pragma unroll 1
                        for (int c = 0; c < 2; c++) {
                            uint32_t L[8] = {}, N[4] = {}, S = 0;
                            constexpr int PK_J0 = 1;
                            PK_FETCH(2 * ti + 1, c);
                            pv_half(L, N, S, bV, (lane >> 3) == 2 * c ? Pf : 0u, (lane >> 3) == 2 * c + 1 ? Pf : 0u, o);
                        }
                    }
                }
                if (cur_seq >= seq) break;
                const uint32_t tb = TAG_BASE(pass);
                l += __shfl_xor_sync(0xffffffffu, l, 1);
                l += __shfl_xor_sync(0xffffffffu, l, 2);
                float m0 = __shfl_sync(0xffffffffu, m, 0), m1 = __shfl_sync(0xffffffffu, m, 4);
                float l0 = __shfl_sync(0xffffffffu, l, 0), l1 = __shfl_sync(0xffffffffu, l, 4);
                const int hid = pass * 8 + cur_seq;
                uint32_t idx = 0;
                if (lane == 0) idx = atomicAdd(reinterpret_cast<unsigned int*>(smem + SM_ARR) + hid, 1u);
                idx = __shfl_sync(0xffffffffu, idx, 0);
                if (idx != 0) mbar_wait(sb + SM_CH + (idx - 1) * 8, hid & 1);
                else if (hid != 0) mbar_wait(sb + SM_CH + 56, (hid - 1) & 1);
                if (idx != 0) {
                    const float4 aml = *reinterpret_cast<const float4*>(accml);
                    const float am0 = aml.x, am1 = aml.y, al0 = aml.z, al1 = aml.w;
                    float n0 = fmaxf(m0, am0), n1 = fmaxf(m1, am1);
                    float sa0 = ex2((am0 - n0) * SCALE_LOG2E), sb0 = ex2((m0 - n0) * SCALE_LOG2E);
                    float sa1 = ex2((am1 - n1) * SCALE_LOG2E), sb1 = ex2((m1 - n1) * SCALE_LOG2E);
                    m0 = n0; m1 = n1;
                    l0 = l0 * sb0 + al0 * sa0; l1 = l1 * sb1 + al1 * sa1;
#pragma unroll
                    for (int i = 0; i < 16; i += 4) {
                        const float4 v = reinterpret_cast<const float4*>(acc)[i * 8 + lane];
                        o[i] = o[i] * sb0 + v.x * sa0; o[i + 1] = o[i + 1] * sb1 + v.y * sa1;
                        o[i + 2] = o[i + 2] * sb0 + v.z * sa0; o[i + 3] = o[i + 3] * sb1 + v.w * sa1;
                    }
                    __syncwarp();
                }
                if (idx != 7) {
#pragma unroll
                    for (int i = 0; i < 16; i += 4) reinterpret_cast<float4*>(acc)[i * 8 + lane] = make_float4(o[i], o[i + 1], o[i + 2], o[i + 3]);
                    if (lane == 0) *reinterpret_cast<float4*>(accml) = make_float4(m0, m1, l0, l1);
                    __syncwarp();
                }
                const bool qfetch = idx == 7 && cur_seq < 6;
                if (lane == 0 && !qfetch) mbar_arrive(sb + SM_CH + idx * 8);
                if (idx == 7) {
                    uint4* dst = g_part + ((cur_seq & 3) * G + cta) * 128 + lane;
                    const float r0 = rcp_fast(l0), r1 = rcp_fast(l1);
                    const float e0 = fmaf(m0, SCALE_LOG2E, lg2(l0)), e1 = fmaf(m1, SCALE_LOG2E, lg2(l1));
#pragma unroll
                    for (int hb = 0; hb < 4; hb++) {
                        const int h = hb >> 1, b = hb & 1;
                        const float r = h ? r1 : r0;
                        part_store(dst + hb * 32, o[2 * b + h] * r, o[4 + 2 * b + h] * r, o[8 + 2 * b + h] * r, o[12 + 2 * b + h] * r,
                                   h ? e1 : e0, tb + TAG_PART + cur_seq);
                    }
                }
                if (qfetch) {
                    const uint4* src = g_q + ((cur_seq + 2) ^ hx) * 128 + lane;
                    uint4 v[4];
                    int it = 0;
                    while (true) {
                        bool ok = true;
#pragma unroll
                        for (int k = 0; k < 4; k++) v[k] = pk_load(src + k * 32);
#pragma unroll
                        for (int k = 0; k < 4; k++) ok = ok && (v[k].z >> 16) == tb + TAG_Q;
                        if (__all_sync(0xffffffffu, ok)) break;
                        if (++it > SPIN_LIMIT) __trap();
                    }
#pragma unroll
                    for (int k = 0; k < 4; k++) q_store(smem + SM_QF + (cur_seq & 1) * 1024, lane + k * 32, v[k]);
                    __syncwarp();
                    if (lane == 0) mbar_arrive(sb + SM_CH + 56);
                }
                if (idx == 0 && cur_seq >= 1) {
                    const uint4* po = g_part + (((cur_seq - 1) & 3) * G + lane) * 128 + (cta & 127);
                    const uint32_t t16 = tb + TAG_PART + cur_seq - 1;
                    const bool last = lane + 128 < G;
                    uint4 v[5];
                    v[4] = make_uint4(0, 0, t16 << 16, __float_as_uint(M_INIT));
                    int it = 0;
                    while (true) {
#pragma unroll
                        for (int k = 0; k < 4; k++) v[k] = pk_load(po + k * 32 * 128);
                        if (last) v[4] = pk_load(po + 128 * 128);
                        bool ok = true;
#pragma unroll
                        for (int k = 0; k < 5; k++) ok = ok && (v[k].z >> 16) == t16;
                        if (__all_sync(0xffffffffu, ok)) break;
                        if (++it > SPIN_LIMIT) __trap();
                    }
                    float gm = M_INIT;
#pragma unroll
                    for (int k = 0; k < 5; k++) gm = fmaxf(gm, __uint_as_float(v[k].w));
                    gm = warp_max(gm);
                    float cw = 0.f, c0 = 0.f, c1 = 0.f, c2 = 0.f, c3 = 0.f;
#pragma unroll
                    for (int k = 0; k < 5; k++) { const float w = ex2(__uint_as_float(v[k].w) - gm); cw += w; part_decode(v[k], w, c0, c1, c2, c3); }
                    warp_sum5(cw, c0, c1, c2, c3);
                    if (lane == 0) {
                        const float rl = rcp_fast(cw);
                        *reinterpret_cast<uint2*>(oc + ((cur_seq - 1) ^ hx) * 2) = make_uint2(pack_bf16(c0 * rl, c1 * rl), pack_bf16(c2 * rl, c3 * rl));
                    }
                }
#pragma unroll
                for (int i = 0; i < 16; i++) o[i] = 0.f;
                m = M_INIT; l = 0.f;
                cur_seq++;
                res_state = ((cur_seq ^ hx ^ warp) & 6) ? 0 : 2;
            }
            if (!more) break;
            const uint32_t ph = ps & 1;
            float s0, s1;
            const bool calt = ps & 4;
            const int cr = rsv ? NS + cta * 8 + warp : pass ? 2 * NS - 1 - pcur : pcur;
            const bool cmark = pass ? ((uint32_t)cr % JUNK_M == 1) : KEEP_POS(cr);
            mbar_wait(barK, ph);
            if (calt && lane == 0) {
                mbar_expect_tx(barV, 4096);
                tma_tile(slotV, &tmV, (cr + ((cur_seq ^ hx) + 1) * RPH) * 8, barV, cmark ? pol_normal() : pol_first());
            }
            uint32_t k = 1, tnext = 0;
            int pn = pcur;
            if (!rsv) pn = take_position(stw, lane, k, tnext);
            if (pn < pcur) __trap();
            fin = rsv && pass == 0;
            const bool nrsv = pass == 0 && pn >= NS;
            const bool nvalid = pn < 2 * NS && lane == 0 && !fin;
            const int pr = nrsv ? NS + cta * 8 + warp : pn >= NS ? 2 * NS - 1 - pn : pn;
            const int nhead = (int)__umulhi((uint32_t)pr, hmagic);
            const int nrow = (pr + (nhead + 1) * RPH) * 8;
            const bool alt = !nrsv && ALT_POS(pn) && res_state != 0 && nhead == (cur_seq ^ hx);
            const bool keep = KEEP_POS(pr);
            const uint64_t pol = (pn < NS ? keep : (!nrsv && (uint32_t)pr % JUNK_M == 1)) ? pol_normal() : pol_first();
            const bool demote = pass == 0 && cmark;
            const uint32_t doff = (uint32_t)(pcur + (cur_seq + 1) * RPH) * 4096u + lane * 128u;
            if (demote) cp_async4_hint(sb + SM_DUM + lane * 4, reinterpret_cast<const char*>(prm.kc) + doff, pol_first());
            if (!fin) ps = pn * 8 + (alt ? 4 : 0) + (nrsv ? 2 : 0) + (ph ^ 1);
            qk_smem(slotK + lmoff, qlane + (cur_seq & 1) * 1024, s0, s1);
            if (nvalid && !alt) { mbar_expect_tx(barK, 4096); tma_tile(slotK, &tmK, nrow, barK, pol); }
            uint32_t P = softmax_step(s0, s1, m, l, o, lane);
            mbar_wait(barV, ph);
            if (nvalid && alt) { mbar_expect_tx(barK, 4096); tma_tile(slotK, &tmK, nrow, barK, pol); }
            if (demote) cp_async4_hint(sb + SM_DUM + lane * 4, reinterpret_cast<const char*>(prm.vc) + doff, pol_first());
            pv_smem(slotV + lmoff, P, o, lane);
            if (nvalid && !alt) { mbar_expect_tx(barV, 4096); tma_tile(slotV, &tmV, nrow, barV, pol); }
            take_publish(stw, lane, k, tnext, G);
            __syncwarp();
            if (res_state == 0) res_state = 1;
        }
        __syncwarp();
        if (lane == 0) stw[warp] = ps;
        }
        asm volatile("cp.async.wait_group 0;" ::: "memory");
        __syncthreads();
        if (cta < NMLP && tid_now() == 225) {
            l2_prefetch(reinterpret_cast<const char*>(prm.w1) + cta * 14336, 14336, pol_normal());
            l2_prefetch(reinterpret_cast<const char*>(prm.w2) + cta * 14336, 14336, pol_normal());
            if (pass == 0) l2_prefetch(reinterpret_cast<const char*>(prm.wq) + cta * 32768, 32768, pol_first());
        }

        if (cta < 128) {
            PHASE_IDS
            const uint32_t tb = TAG_BASE(pass);
            const int t = lane & 3;
            const uint4* e1src = g_part + (3 * G + tid) * 128 + cta;
            uint4 pv = make_uint4(0, 0, 0, __float_as_uint(M_INIT));
            if (warp < 7) {
                float r0 = 0.f, r1 = 0.f;
                uint32_t wl[4];
                {
                    const uint32_t woa = sb + SM_WO + ((lane & 7) + 8 * (lane >> 4)) * W2_PITCH + warp * 128 + ((lane >> 3) & 1) * 16;
                    uint32_t b0 = oc[t], b1 = oc[4 + t], b2 = oc[8 + t], b3 = oc[12 + t];
                    if (pass == 0) { if (t >= 2) b3 = 0; } else { if (t < 2) b0 = 0; }
#pragma unroll
                    for (int j = 0; j < 4; j++) {
                        uint32_t aa[4], ab[4];
                        ldsm4t(aa, woa + j * 32);
                        ldsm4t(ab, woa + 16 * W2_PITCH + j * 32);
                        float d[4] = {0.f, 0.f, 0.f, 0.f};
                        mma16816(d, aa, b0, b1);
                        mma16816(d, ab, b2, b3);
                        if (t == j) { r0 = d[0]; r1 = d[2]; }
                    }
                    const unsigned short* wp = reinterpret_cast<const unsigned short*>(smem + SM_WO + (pass ? 0 : 28) * W2_PITCH) + (warp * 4 + t) * 16 + (lane >> 2);
#pragma unroll
                    for (int r = 0; r < 4; r++) wl[r] = (uint32_t)wp[r * (W2_PITCH / 2)] | ((uint32_t)wp[r * (W2_PITCH / 2) + 8] << 16);
                }
                if (warp < MAXG / 32) {
                    pv = pk_poll(e1src, tid < G, tb + TAG_PART + 7, pv);
                    const float cm = warp_max(__uint_as_float(pv.w));
                    float cl = tid < G ? ex2(__uint_as_float(pv.w) - cm) : 0.f, c0 = 0.f, c1 = 0.f, c2 = 0.f, c3 = 0.f;
                    part_decode(pv, cl, c0, c1, c2, c3);
                    warp_sum5(cl, c0, c1, c2, c3);
                    if (lane == 0) {
                        *reinterpret_cast<float4*>(sc + 32 + warp * 8) = make_float4(c0, c1, c2, c3);
                        *reinterpret_cast<float2*>(sc + 32 + warp * 8 + 4) = make_float2(cm, cl);
                    }
                }
                cta_sync();
                {
                    constexpr int NW = MAXG / 32;
                    float2 ml[NW];
#pragma unroll
                    for (int w = 0; w < NW; w++) ml[w] = *reinterpret_cast<const float2*>(sc + 32 + w * 8 + 4);
                    const float gm = fmaxf(fmaxf(fmaxf(ml[0].x, ml[1].x), fmaxf(ml[2].x, ml[3].x)), ml[4].x);
                    float cl = 0.f, c0 = 0.f, c1 = 0.f, c2 = 0.f, c3 = 0.f;
#pragma unroll
                    for (int w = 0; w < NW; w++) {
                        const float4 v = *reinterpret_cast<const float4*>(sc + 32 + w * 8);
                        const float wv = ex2(ml[w].x - gm);
                        cl = fmaf(ml[w].y, wv, cl);
                        c0 = fmaf(v.x, wv, c0); c1 = fmaf(v.y, wv, c1); c2 = fmaf(v.z, wv, c2); c3 = fmaf(v.w, wv, c3);
                    }
                    const float rl = rcp_fast(cl);
                    c0 = bf16r(c0 * rl); c1 = bf16r(c1 * rl); c2 = bf16r(c2 * rl); c3 = bf16r(c3 * rl);
                    r0 = fmaf(c0, bf_lo(wl[0]), fmaf(c1, bf_lo(wl[1]), r0)) + fmaf(c2, bf_lo(wl[2]), c3 * bf_lo(wl[3]));
                    r1 = fmaf(c0, bf_hi(wl[0]), fmaf(c1, bf_hi(wl[1]), r1)) + fmaf(c2, bf_hi(wl[2]), c3 * bf_hi(wl[3]));
                    pk_store(g_part + ((warp * 4 + t) * 4 + 2 * (lane >> 4) + ((lane >> 2) & 1)) * 256 + cta * 2 + ((lane >> 3) & 1),
                             __float_as_uint(r0), __float_as_uint(r1), (tb + TAG_R1) << 16, 0);
                }
                if (cta < NMLP) {
                uint32_t a1f[8][2], a2f[4][4];
#pragma unroll
                for (int j = 0; j < 8; j++) { const uint2 v = ldg64(W1_SRC(j)); a1f[j][0] = v.x; a1f[j][1] = v.y; }
#pragma unroll
                for (int j = 0; j < 8; j++) { a1f[j][0] = movtrans(a1f[j][0]); a1f[j][1] = movtrans(a1f[j][1]); }
                cta_sync();
#pragma unroll
                for (int j = 0; j < 4; j++) { const uint4 v = ldg128(W2_SRC(j)); a2f[j][0] = v.x; a2f[j][1] = v.y; a2f[j][2] = v.z; a2f[j][3] = v.w; }
                spin_clk(DLY_X);
                const uint4 xv = pk_poll(g_x + warp * 16 + lane, lane < 16, tb + TAG_X1, make_uint4(0, 0, 0, 0));
                {
                    const bool ones = (lane >> 2) == 1;
                    float d0[4] = {0.f, 0.f, 0.f, 0.f}, ds[4] = {0.f, 0.f, 0.f, 0.f}, d1[4] = {0.f, 0.f, 0.f, 0.f}, dt[4] = {0.f, 0.f, 0.f, 0.f};
#pragma unroll
                    for (int j = 0; j < 4; j++) {
                        const uint32_t x0 = __shfl_sync(0xffffffffu, xv.x, j * 4 + (lane & 3)), x1 = __shfl_sync(0xffffffffu, xv.y, j * 4 + (lane & 3));
                        const uint32_t b0 = ones ? 0x3f803f80u : x0, b1 = ones ? 0x3f803f80u : x1;
                        const uint32_t a0[4] = {a1f[2 * j][0], a1f[2 * j][1], a1f[2 * j + 1][0], a1f[2 * j + 1][1]};
                        const uint32_t a2[4] = {0x3f803f80u, x0, 0x3f803f80u, x1};
                        mma16816((j & 1) ? d1 : d0, a0, b0, b1);
                        mma16816((j & 1) ? dt : ds, a2, b0, b1);
                    }
                    if ((lane & 3) == 0) {
                        const int g = lane >> 2;
                        float2* pp = reinterpret_cast<float2*>(acc) + warp * 16 + 4 * (g >> 1) + (g & 1);
                        pp[0] = make_float2(d0[0] + d1[0], d0[1] + d1[1]); pp[2] = make_float2(d0[2] + d1[2], d0[3] + d1[3]);
                        if (lane == 0) *reinterpret_cast<float2*>(sc + 96 + 2 * warp) = ln_partial(ds[0] + dt[0], ds[2] + dt[2]);
                    }
                }
#pragma unroll
                for (int j = 0; j < 4; j++) {
#pragma unroll
                    for (int r = 0; r < 4; r++) a2f[j][r] = movtrans(a2f[j][r]);
                }
                cta_sync();
                float mb, rsd;
                ln_stats(sc + 96, mb, rsd);
                float2 v[7];
#pragma unroll
                for (int w = 0; w < 7; w++) v[w] = *reinterpret_cast<const float2*>(acc + w * 32 + (lane & 15) * 2);
                const float hs = ((v[0].x + v[1].x) + (v[2].x + v[3].x)) + ((v[4].x + v[5].x) + v[6].x);
                const float ws = ((v[0].y + v[1].y) + (v[2].y + v[3].y)) + ((v[4].y + v[5].y) + v[6].y);
                const float hv = bf16r(bf16r(fmaf(-mb, ws, hs) * rsd) + xk[8 + (lane & 15)]);
                const float gl = hv * rcp_fast(1.0f + ex2(hv * fmaf(hv * hv, -0.044715f * 2.3022081986f, -2.3022081986f)));
                const uint32_t b0 = pack_bf16(__shfl_sync(0xffffffffu, gl, 2 * t), __shfl_sync(0xffffffffu, gl, 2 * t + 1));
                const uint32_t b1 = pack_bf16(__shfl_sync(0xffffffffu, gl, 2 * t + 8), __shfl_sync(0xffffffffu, gl, 2 * t + 9));
#pragma unroll
                for (int j = 0; j < 4; j++) {
                    const int c2 = j >> 1, r = 2 * (j & 1);
                    const uint32_t a[4] = {a2f[2 * c2][r], a2f[2 * c2][r + 1], a2f[2 * c2 + 1][r], a2f[2 * c2 + 1][r + 1]};
                    float d[4] = {0.f, 0.f, 0.f, 0.f};
                    mma16816(d, a, b0, b1);
                    if (t == j) { r0 = d[0]; r1 = d[2]; }
                }
                pk_store(g_part + ((warp * 4 + 2 * (t >> 1) + (lane >> 4)) * 4 + 2 * (t & 1) + ((lane >> 2) & 1)) * 256 + cta * 2 + ((lane >> 3) & 1),
                         __float_as_uint(r0), __float_as_uint(r1), (tb + TAG_R2) << 16, 0);
                }
            } else {
                cta_sync();
                if (cta >= NMLP) { if (pass == 0) { GAP_PREFETCH(0); GAP_PREFETCH(1); GAP_PREFETCH(2); } } else {
                float s0, s1;
                {
                    const float2 xo = *reinterpret_cast<const float2*>(xk + (lane & 1) * 2);
                    spin_clk(DLY_R1);
                    reduce_packets<8>(RS_SRC, tb + TAG_R1, s0, s1);
                    const uint32_t xw = pack_bf16(xo.x + bf16r(s0), xo.y + bf16r(s1));
                    const uint32_t xw1 = __shfl_down_sync(0xffffffffu, xw, 1);
                    if (lane == 0) pk_store(g_x + cta, xw, xw1, (tb + TAG_X1) << 16, 0);
                    if (lane < 2) *reinterpret_cast<float2*>(xk + lane * 2) = make_float2(bf_lo(xw), bf_hi(xw));
                }
                if (pass == 0) GAP_PREFETCH(0);
                cta_sync();
                cta_sync();
                if (pass == 0) GAP_PREFETCH(1);
                {
                    const float xo0 = xk[lane & 1], xo1 = xk[2 + (lane & 1)], bb0 = xk[4 + (lane & 1)], bb1 = xk[6 + (lane & 1)];
                    spin_clk(DLY_R2);
                    reduce_packets<7>(RS_SRC, tb + TAG_R2, s0, s1);
                    const uint32_t xw = pack_bf16(xo0 + bf16r(bf16r(s0) + bb0), xo1 + bf16r(bf16r(s1) + bb1));
                    if (pass == 0) {
                        const uint32_t xw1 = __shfl_down_sync(0xffffffffu, xw, 1);
                        if (lane == 0) pk_store(g_x + cta, __byte_perm(xw, xw1, 0x5410), __byte_perm(xw, xw1, 0x7632), (tb + TAG_X2) << 16, 0);
                        if (lane < 2) { xk[lane] = bf_lo(xw); xk[2 + lane] = bf_hi(xw); }
                        GAP_PREFETCH(2);
                    } else {
                        unsigned short* op = reinterpret_cast<unsigned short*>(prm.out) + 16 * (cta >> 2) + 4 * ((cta >> 1) & 1) + (cta & 1) + 8 * lane;
                        if (lane < 2) { op[0] = (unsigned short)(xw & 0xffffu); op[2] = (unsigned short)(xw >> 16); }
                        if (cta == 0 && lane == 0) {
                            g_ticket[0] = 0;
                            g_epoch[0] = *epw + 1;
                        }
                    }
                }
                }
            }
        }
    }
}

constexpr int FB_SPLIT = 128, FB_KEYS = SK / FB_SPLIT;
__device__ float fb_x[D_MODEL], fb_v[NQ], fb_h[NQ], fb_part[16 * FB_SPLIT * (DH + 2)];

__device__ float fb_block_sum(float v, float* red) {
    for (int o = 16; o; o >>= 1) v += __shfl_xor_sync(0xffffffffu, v, o);
    __syncthreads();
    if ((threadIdx.x & 31) == 0) red[threadIdx.x >> 5] = v;
    __syncthreads();
    float t = 0.f;
    for (int i = 0; i < 8; i++) t += red[i];
    return t;
}
__global__ void __launch_bounds__(256) fb_gemv(int mode, int first, const __nv_bfloat16* x0, const __nv_bfloat16* W, const __nv_bfloat16* bias,
                                               int K, int N, __nv_bfloat16* dst) {
    __shared__ float y[NQ], red[8];
    const int t = threadIdx.x;
    if (mode < 2) {
        float s = 0.f;
        for (int i = t; i < K; i += 256) { y[i] = first ? __bfloat162float(x0[i]) : fb_x[i]; s += y[i]; }
        const float mean = fb_block_sum(s, red) / K;
        s = 0.f;
        for (int i = t; i < K; i += 256) s += (y[i] - mean) * (y[i] - mean);
        const float sd = bf16r(sqrtf(bf16r(bf16r(fb_block_sum(s, red) / K) + 1e-5f)));
        for (int i = t; i < K; i += 256) y[i] = bf16r(bf16r(y[i] - bf16r(mean)) / sd);
    } else {
        for (int i = t; i < K; i += 256) y[i] = mode == 2 ? fb_v[i] : fb_h[i];
    }
    __syncthreads();
    const int j = blockIdx.x * 8 + (t >> 5);
    float a = 0.f;
    for (int k = t & 31; k < K; k += 32) a = fmaf(y[k], __bfloat162float(W[(size_t)k * N + j]), a);
    for (int o = 16; o; o >>= 1) a += __shfl_xor_sync(0xffffffffu, a, o);
    if (t & 31) return;
    a = bf16r(a);
    if (mode & 1) a = bf16r(a + __bfloat162float(bias[j]));
    if (mode == 0) fb_h[j] = a;
    else if (mode == 1) fb_h[j] = bf16r(0.5f * a * (1.f + tanhf(0.7978845608028654f * (a + 0.044715f * a * a * a))));
    else {
        const float r = bf16r((first ? __bfloat162float(x0[j]) : fb_x[j]) + a);
        fb_x[j] = r;
        if (dst) dst[j] = __float2bfloat16_rn(r);
    }
}
__global__ void __launch_bounds__(256) fb_attn(const __nv_bfloat16* kc, const __nv_bfloat16* vc) {
    __shared__ float sc[FB_KEYS], red[8];
    const int t = threadIdx.x, h = blockIdx.x / FB_SPLIT, sp = blockIdx.x % FB_SPLIT;
    const size_t row0 = (size_t)(h >> 1) * SK + (size_t)sp * FB_KEYS;
    for (int k = t >> 5; k < FB_KEYS; k += 8) {
        float a = 0.f;
        for (int d = t & 31; d < DH; d += 32) a = fmaf(fb_h[h * DH + d], __bfloat162float(kc[(row0 + k) * DH + d]), a);
        for (int o = 16; o; o >>= 1) a += __shfl_xor_sync(0xffffffffu, a, o);
        sc[k] = bf16r(a) * 0.0625f;
    }
    __syncthreads();
    float m = M_INIT;
    for (int k = 0; k < FB_KEYS; k++) m = fmaxf(m, sc[k]);
    __syncthreads();
    float l = 0.f;
    for (int k = t; k < FB_KEYS; k += 256) { sc[k] = __expf(sc[k] - m); l += sc[k]; }
    l = fb_block_sum(l, red);
    float o = 0.f;
    for (int k = 0; k < FB_KEYS; k++) o = fmaf(sc[k], __bfloat162float(vc[(row0 + k) * DH + t]), o);
    float* p = fb_part + (size_t)blockIdx.x * (DH + 2);
    p[t] = o;
    if (t == 0) { p[DH] = m; p[DH + 1] = l; }
}
__global__ void __launch_bounds__(256) fb_combine() {
    const float* p = fb_part + (size_t)blockIdx.x * FB_SPLIT * (DH + 2);
    float m = M_INIT, l = 0.f, o = 0.f;
    for (int s = 0; s < FB_SPLIT; s++) m = fmaxf(m, p[s * (DH + 2) + DH]);
    for (int s = 0; s < FB_SPLIT; s++) {
        const float w = __expf(p[s * (DH + 2) + DH] - m);
        l = fmaf(w, p[s * (DH + 2) + DH + 1], l); o = fmaf(w, p[s * (DH + 2) + threadIdx.x], o);
    }
    fb_v[blockIdx.x * DH + threadIdx.x] = bf16r(o / l);
}
void fallback_launch(const Params& p) {
    cudaStream_t st = cudaStreamPerThread;
    for (int L = 0; L < 2; L++) {
        fb_gemv<<<NQ / 8, 256, 0, st>>>(0, L == 0, p.x0, p.wq, nullptr, D_MODEL, NQ, nullptr);
        fb_attn<<<16 * FB_SPLIT, 256, 0, st>>>(p.kc, p.vc);
        fb_combine<<<16, 256, 0, st>>>();
        fb_gemv<<<D_MODEL / 8, 256, 0, st>>>(2, L == 0, p.x0, p.wo, nullptr, NQ, D_MODEL, nullptr);
        fb_gemv<<<FF / 8, 256, 0, st>>>(1, 0, p.x0, p.w1, p.b1, D_MODEL, FF, nullptr);
        fb_gemv<<<D_MODEL / 8, 256, 0, st>>>(3, 0, p.x0, p.w2, p.b2, FF, D_MODEL, L ? p.out : nullptr);
    }
}

typedef CUresult (*EncodeFn)(CUtensorMap*, CUtensorMapDataType, cuuint32_t, void*, const cuuint64_t*, const cuuint64_t*,
                             const cuuint32_t*, const cuuint32_t*, CUtensorMapInterleave, CUtensorMapSwizzle,
                             CUtensorMapL2promotion, CUtensorMapFloatOOBfill);

void make_map(EncodeFn fn, CUtensorMap* m, const void* base) {
    cuuint64_t dims[3] = {64, (cuuint64_t)NROWS, 4};
    cuuint64_t strides[2] = {512, 128};
    cuuint32_t box[3] = {64, 8, 4};
    cuuint32_t es[3] = {1, 1, 1};
    fn(m, CU_TENSOR_MAP_DATA_TYPE_BFLOAT16, 3, const_cast<void*>(base), dims, strides, box, es,
       CU_TENSOR_MAP_INTERLEAVE_NONE, CU_TENSOR_MAP_SWIZZLE_128B, CU_TENSOR_MAP_L2_PROMOTION_L2_128B,
       CU_TENSOR_MAP_FLOAT_OOB_FILL_NONE);
}

}

extern "C" void kernel_launch(void* const* d_in, const int* in_sizes, int n_in, void* d_out, int out_size) {
    (void)in_sizes; (void)n_in; (void)out_size;
    static EncodeFn fn = nullptr;
    static int nsm = -1;
    if (nsm < 0) {
        cudaDriverEntryPointQueryResult st;
        cudaGetDriverEntryPoint("cuTensorMapEncodeTiled", (void**)&fn, cudaEnableDefault, &st);
        int dev = 0;
        cudaGetDevice(&dev);
        cudaDeviceGetAttribute(&nsm, cudaDevAttrMultiProcessorCount, dev);
        if (nsm > MAXG) nsm = MAXG;
        if (cudaFuncSetAttribute(fused_kernel, cudaFuncAttributeMaxDynamicSharedMemorySize, SM_TOTAL) != cudaSuccess) {
            (void)cudaGetLastError();
            nsm = 0;
        }
    }
    Params p;
    p.x0 = (const __nv_bfloat16*)d_in[0];
    p.kc = (const __nv_bfloat16*)d_in[1];
    p.vc = (const __nv_bfloat16*)d_in[2];
    p.wq = (const __nv_bfloat16*)d_in[3];
    p.wo = (const __nv_bfloat16*)d_in[4];
    p.w1 = (const __nv_bfloat16*)d_in[6];
    p.b1 = (const __nv_bfloat16*)d_in[7];
    p.w2 = (const __nv_bfloat16*)d_in[8];
    p.b2 = (const __nv_bfloat16*)d_in[9];
    p.out = (__nv_bfloat16*)d_out;
    if (fn && nsm >= 128) {
        const uint64_t per_head = (uint64_t)(SK / 8 - nsm * 6);
        p.hmagic = (uint32_t)((0x100000000ull + per_head - 1) / per_head);
        CUtensorMap tmK, tmV;
        make_map(fn, &tmK, d_in[1]);
        make_map(fn, &tmV, d_in[2]);
        void* args[] = {&tmK, &tmV, &p};
        cudaLaunchCooperativeKernel((const void*)fused_kernel, dim3(nsm), dim3(NTHREADS), args, SM_TOTAL, cudaStreamPerThread);
        return;
    }
    p.hmagic = 0;
    fallback_launch(p);
}
```
